```python
import torch

def _softmax(x, axis=-1):
    return torch.softmax(x, dim=axis)
def _gelu(x):
    return torch.nn.functional.gelu(x, approximate="tanh")
def _silu(x):
    return torch.nn.functional.silu(x)
def _sigmoid(x):
    return torch.sigmoid(x)
def _layernorm(x, axis=-1, eps=1e-5):
    m = x.mean(dim=axis, keepdim=True)
    v = x.var(dim=axis, keepdim=True, unbiased=False)
    return (x - m) / torch.sqrt(v + eps)
def _scatter_add(tgt, idx, src, axis=0):
    return tgt.clone().index_add_(axis, idx, src)
def _segment_sum(src, seg, n):
    out = torch.zeros((n,) + src.shape[1:], dtype=src.dtype)
    return out.index_add_(0, seg, src)
def _pad(x, pw):
    flat = tuple(v for pair in reversed(pw) for v in pair)
    return torch.nn.functional.pad(x, flat)

kernel_name = 'gated_mix__linear_kernel_hedgehog__mha_block__prompt'

def setup_inputs():

    _w = (lambda a: (lambda t: t.to(torch.bfloat16) if t.is_floating_point() else t)(torch.as_tensor(a)))
    def _A_setup():
        B, S, D, H = 1, 2048, 640, 32
        Dh = D // H
        return {
            "x": _w((lambda *s: torch.randn(*s, dtype=torch.bfloat16) * 0.05)(B, S, D)),
            "wqkv": _w((lambda *s: torch.randn(*s, dtype=torch.bfloat16) * 1.6)(D, 3 * D)),
            "w_phi": _w((lambda *s: torch.randn(*s, dtype=torch.bfloat16) * 1.6)(H, Dh, Dh) * (Dh ** -0.5)),
            "wo": _w((lambda *s: torch.randn(*s, dtype=torch.bfloat16) * 0.05)(D, D)),
        }
    _A_in = _A_setup()

    def _B_setup():
        B, S, D, H = 1, 2048, 640, 32
        return {
            "x": _w((lambda *s: torch.randn(*s, dtype=torch.bfloat16) * 0.05)(B, S, D)),
            "wqkv": _w((lambda *s: torch.randn(*s, dtype=torch.bfloat16) * 0.8)(D, 3 * D)),
            "wo": _w((lambda *s: torch.randn(*s, dtype=torch.bfloat16) * 0.05)(D, D)),
        }
    _B_in = _B_setup()

    return {
        "A_x": _A_in["x"],
        "A_wqkv": _A_in["wqkv"],
        "A_w_phi": _A_in["w_phi"],
        "A_wo": _A_in["wo"],
        "B_x": _B_in["x"],
        "B_wqkv": _B_in["wqkv"],
        "B_wo": _B_in["wo"],
        "gate_w": _w((lambda *s: torch.randn(*s, dtype=torch.bfloat16) * 0.05)(640) * 16.0),
    }

def reference(A_x, A_wqkv, A_w_phi, A_wo, B_x, B_wqkv, B_wo, gate_w):
    def _A_ref(x, wqkv, w_phi, wo):
        B, S, D = x.shape
        H = 32; Dh = D // H
        qkv = (lambda x, *d: x.permute(*d))((x @ wqkv).reshape(B, S, 3, H, Dh), 2, 0, 3, 1, 4)
        q, k, v = qkv[0], qkv[1], qkv[2]
        pq = torch.einsum("bhsd,hdf->bhsf", q, w_phi)
        pk = torch.einsum("bhsd,hdf->bhsf", k, w_phi)
        phi_q = torch.concatenate([_softmax(pq, axis=-1), _softmax(-pq, axis=-1)], axis=-1)
        phi_k = torch.concatenate([_softmax(pk, axis=-1), _softmax(-pk, axis=-1)], axis=-1)
        kv = torch.einsum("bhsf,bhsd->bhfd", phi_k, v)
        z  = torch.einsum("bhsf->bhf", phi_k)
        num = torch.einsum("bhqf,bhfd->bhqd", phi_q, kv)
        den = torch.einsum("bhqf,bhf->bhq", phi_q, z)[..., None] + 1e-6
        o = num / den
        return (lambda x, *d: x.permute(*d))(o, 0, 2, 1, 3).reshape(B, S, D) @ wo

    def _B_ref(x, wqkv, wo):
        B, S, D = x.shape
        H = 32
        Dh = D // H
        qkv = (lambda x, *d: x.permute(*d))((x @ wqkv).reshape(B, S, 3, H, Dh), 2, 0, 3, 1, 4)
        q, k, v = qkv[0], qkv[1], qkv[2]
        scores = torch.einsum("bhqd,bhkd->bhqk", q, k) * (Dh ** -0.5)
        p = _softmax(scores, axis=-1)
        o = torch.einsum("bhqk,bhkd->bhqd", p, v)
        return (lambda x, *d: x.permute(*d))(o, 0, 2, 1, 3).reshape(B, S, D) @ wo

    x = A_x
    g = _sigmoid((x * gate_w).sum(-1, keepdims=True))
    a = _A_ref(x, A_wqkv, A_w_phi, A_wo)
    b = _B_ref(x, B_wqkv, B_wo)
    return g * a + (1 - g) * b
```

```cpp
#include <cuda_runtime.h>
#include <cuda_bf16.h>
#include <cuda_fp16.h>
#include <cuda.h>
#include <stdint.h>
#include <stdio.h>

#define STOPS0 0x82A0u
#define STOPS1 0x84C0u
#define DONEU 1
#define NPRE 13
#define SIGFIRST 0
namespace {

constexpr int S_ = 2048, D_ = 640, H_ = 32;
constexpr int SLICE = 6144;
constexpr int KVB = 2 * SLICE;
#define PMASKV 0xADADu
constexpr uint32_t PMASK = PMASKV;
constexpr float QSCALE = 0.32259298f;

__device__ __align__(1024) uint8_t g_qB[H_ * 16 * SLICE];
__device__ __align__(1024) uint8_t g_kvB[H_ * 16 * KVB];
__device__ __align__(1024) uint8_t g_A[3 * H_ * 16 * SLICE];
__device__ __align__(1024) uint8_t g_o[16 * 160 * 2048];
__device__ __align__(1024) uint8_t g_wo[8 * 20 * 10240];
__device__ __align__(128) float g_stat[H_ * 32];
__device__ __align__(16) float g_gate[S_];
__device__ __align__(16) float g_kvs[H_ * 40 * 24];
__device__ __align__(16) __nv_bfloat16 g_fb[H_ * S_ * 40];
constexpr int C_B = 0, C_EXIT = 64, C_OA = 96, C_KV = 224, C_A = C_KV + 32 * 32, C_OB = C_A + 4, C_N = C_A + 128 * 8;
__device__ __align__(128) unsigned int g_cnt[C_N];

#define TS(k, i) do {} while (0)
#define TQ(i) do {} while (0)
__device__ __forceinline__ uint32_t smem_u32(const void* p) { return (uint32_t)__cvta_generic_to_shared(p); }
__device__ __forceinline__ uint64_t mkdesc(uint32_t a16, uint32_t lbo, uint32_t sbo, uint32_t swz) {
  uint32_t lo = a16 + ((lbo >> 4) << 16);
  uint32_t hi = (sbo >> 4) | (swz << 30);
  return ((uint64_t)hi << 32) | lo;
}
template <int INC> __device__ __forceinline__ uint64_t addlo(uint64_t d) {
  asm volatile("{.reg .b32 lo, hi; mov.b64 {lo,hi}, %0; add.u32 lo, lo, %1; mov.b64 %0, {lo,hi};}" : "+l"(d) : "n"(INC));
  return d;
}
__device__ __forceinline__ uint64_t addlo_r(uint64_t d, uint32_t inc) {
  asm volatile("{.reg .b32 lo, hi; mov.b64 {lo,hi}, %0; add.u32 lo, lo, %1; mov.b64 %0, {lo,hi};}" : "+l"(d) : "r"(inc));
  return d;
}
__device__ __forceinline__ void wg_fence() { asm volatile("wgmma.fence.sync.aligned;" ::: "memory"); }
__device__ __forceinline__ void wg_commit() { asm volatile("wgmma.commit_group.sync.aligned;" ::: "memory"); }
template <int N> __device__ __forceinline__ void wg_wait() { asm volatile("wgmma.wait_group.sync.aligned %0;" ::"n"(N) : "memory"); }
template <int N> __device__ __forceinline__ void fence_f(float* r) {
#pragma unroll
  for (int i = 0; i < N; i++) asm volatile("" : "+f"(r[i])::"memory");
}
template <int N> __device__ __forceinline__ void fence_u(uint32_t* r) {
#pragma unroll
  for (int i = 0; i < N; i++) asm volatile("" : "+r"(r[i])::"memory");
}
__device__ __forceinline__ void mbar_init(uint32_t bar, uint32_t cnt) { asm volatile("mbarrier.init.shared::cta.b64 [%0], %1;" ::"r"(bar), "r"(cnt) : "memory"); }
__device__ __forceinline__ void mbar_expect_tx(uint32_t bar, uint32_t bytes) { asm volatile("mbarrier.arrive.expect_tx.shared::cta.b64 _, [%0], %1;" ::"r"(bar), "r"(bytes) : "memory"); }
__device__ __forceinline__ void mbar_wait(uint32_t bar, uint32_t parity) {
  asm volatile(
      "{\n.reg .pred p;\n.reg .u32 n;\nmov.u32 n, 0;\n"
      "W: mbarrier.try_wait.parity.shared::cta.b64 p, [%0], %1;\n@p bra D;\n"
      "add.u32 n, n, 1;\nsetp.lt.u32 p, n, 0x1000000;\n@p bra W;\ntrap;\nD:\n}" ::"r"(bar), "r"(parity) : "memory");
}
__device__ __forceinline__ bool mbar_test_wg(uint32_t bar, uint32_t parity, int id) {
  uint32_t r;
  asm volatile("{.reg .pred p, q; mbarrier.test_wait.parity.shared::cta.b64 p, [%1], %2; bar.red.and.pred q, %3, 128, p; selp.u32 %0, 1, 0, q;}"
               : "=r"(r) : "r"(bar), "r"(parity), "r"(id) : "memory");
  return r != 0;
}
__device__ __forceinline__ void mbar_wait_z(uint32_t bar, uint32_t parity) {
  asm volatile(
      "{\n.reg .pred p;\n.reg .u32 n;\nmov.u32 n, 0;\n"
      "W: mbarrier.try_wait.parity.shared::cta.b64 p, [%0], %1, 20000;\n@p bra D;\n"
      "add.u32 n, n, 1;\nsetp.lt.u32 p, n, 0x100000;\n@p bra W;\ntrap;\nD:\n}" ::"r"(bar), "r"(parity) : "memory");
}
__device__ __forceinline__ void mbar_wait_u(uint32_t bar, uint32_t parity) {
  asm volatile("{\n.reg .pred p;\nW: mbarrier.try_wait.parity.shared::cta.b64 p, [%0], %1;\n@p bra D;\nbra W;\nD:\n}" ::"r"(bar), "r"(parity) : "memory");
}
__device__ __forceinline__ void mbar_arrive_cluster(uint32_t bar, uint32_t cta) {
  asm volatile("{.reg .b32 r; mapa.shared::cluster.u32 r, %0, %1; mbarrier.arrive.shared::cluster.b64 _, [r];}" ::"r"(bar), "r"(cta) : "memory");
}
__device__ __forceinline__ void bulk_g2s(uint32_t dst, const void* src, uint32_t bytes, uint32_t bar) {
  asm volatile("cp.async.bulk.shared::cluster.global.mbarrier::complete_tx::bytes [%0], [%1], %2, [%3];" ::"r"(dst), "l"(src), "r"(bytes), "r"(bar) : "memory");
}
__device__ __forceinline__ void bulk_g2s_mc(uint32_t dst, const void* src, uint32_t bytes, uint32_t bar, uint16_t mask) {
  asm volatile("cp.async.bulk.shared::cluster.global.mbarrier::complete_tx::bytes.multicast::cluster [%0], [%1], %2, [%3], %4;" ::"r"(dst), "l"(src), "r"(bytes), "r"(bar), "h"(mask) : "memory");
}
__device__ __forceinline__ void bulk_s2g(void* dst, uint32_t src, uint32_t bytes) {
  asm volatile("cp.async.bulk.global.shared::cta.bulk_group [%0], [%1], %2;" ::"l"(dst), "r"(src), "r"(bytes) : "memory");
}
__device__ __forceinline__ void tma2d(uint32_t dst, const CUtensorMap* m, int c0, int c1, uint32_t bar) {
  asm volatile("cp.async.bulk.tensor.2d.shared::cluster.global.mbarrier::complete_tx::bytes [%0], [%1, {%3, %4}], [%2];" ::"r"(dst), "l"(m), "r"(bar), "r"(c0), "r"(c1) : "memory");
}
__device__ __forceinline__ void tma2d_mc(uint32_t dst, const CUtensorMap* m, int c0, int c1, uint32_t bar, uint16_t mask) {
  asm volatile("cp.async.bulk.tensor.2d.shared::cluster.global.mbarrier::complete_tx::bytes.multicast::cluster [%0], [%1, {%3, %4}], [%2], %5;" ::"r"(dst), "l"(m), "r"(bar), "r"(c0), "r"(c1), "h"(mask) : "memory");
}
__device__ __forceinline__ void tma2d_store(const CUtensorMap* m, uint32_t src, int c0, int c1) {
  asm volatile("cp.async.bulk.tensor.2d.global.shared::cta.bulk_group [%0, {%2, %3}], [%1];" ::"l"(m), "r"(src), "r"(c0), "r"(c1) : "memory");
}
__device__ __forceinline__ void bulk_commit() { asm volatile("cp.async.bulk.commit_group;" ::: "memory"); }
__device__ __forceinline__ void bulk_wait_all() { asm volatile("cp.async.bulk.wait_group 0;" ::: "memory"); }
__device__ __forceinline__ void fence_async() { asm volatile("fence.proxy.async.shared::cta;" ::: "memory"); }
__device__ __forceinline__ void bar_sync(int id, int n) { asm volatile("bar.sync %0, %1;" ::"r"(id), "r"(n) : "memory"); }
__device__ __forceinline__ void cluster_sync() { asm volatile("barrier.cluster.arrive.aligned; barrier.cluster.wait.aligned;" ::: "memory"); }
__device__ __forceinline__ void bar_arrive(int id, int n) { asm volatile("bar.arrive %0, %1;" ::"r"(id), "r"(n) : "memory"); }
__device__ __forceinline__ void mbar_arrive(uint32_t bar) { asm volatile("mbarrier.arrive.shared::cta.b64 _, [%0];" ::"r"(bar) : "memory"); }
__device__ __forceinline__ void fence_gpu() { asm volatile("fence.acq_rel.gpu;" ::: "memory"); }
__device__ __forceinline__ void fence_async_g() { asm volatile("fence.proxy.async.global;" ::: "memory"); }
__device__ __forceinline__ void signal(int c) { fence_gpu(); asm volatile("red.relaxed.gpu.global.add.u32 [%0], 1;" ::"l"(g_cnt + c) : "memory"); }
__device__ __forceinline__ void await(int c, uint32_t target) {
  asm volatile(
      "{\n.reg .pred p;\n.reg .u32 n, v;\nmov.u32 n, 0;\n"
      "W: ld.acquire.gpu.global.u32 v, [%0];\nsetp.ge.u32 p, v, %1;\n@p bra D;\n"
      "nanosleep.u32 64;\nadd.u32 n, n, 1;\nsetp.lt.u32 p, n, 0x400000;\n@p bra W;\ntrap;\nD:\n}" ::"l"(g_cnt + c), "r"(target) : "memory");
}
__device__ __forceinline__ void await_all(int c, uint32_t target) {
  asm volatile(
      "{\n.reg .pred p;\n.reg .u32 n, v;\nmov.u32 n, 0;\n"
      "W: ld.acquire.gpu.global.u32 v, [%0];\nsetp.ge.u32 p, v, %1;\nvote.sync.all.pred p, p, 0xffffffff;\n@p bra.uni D;\n"
      "nanosleep.u32 64;\nadd.u32 n, n, 1;\nsetp.lt.u32 p, n, 0x400000;\n@p bra.uni W;\ntrap;\nD:\n}" ::"l"(g_cnt + c), "r"(target) : "memory");
}
__device__ __forceinline__ uint32_t await_mask(int c, uint32_t need) {
  uint32_t m;
  asm volatile(
      "{\n.reg .pred p;\n.reg .u32 n, v;\nmov.u32 n, 0;\n"
      "W: ld.acquire.gpu.global.u32 v, [%1];\nsetp.ne.u32 p, v, 0;\nvote.sync.ballot.b32 %0, p, 0xffffffff;\n"
      "and.b32 v, %0, %2;\nsetp.eq.u32 p, v, %2;\n@p bra.uni D;\n"
      "add.u32 n, n, 1;\nsetp.lt.u32 p, n, 0x400000;\n@p bra.uni W;\ntrap;\nD:\n}" : "=r"(m) : "l"(g_cnt + c), "r"(need) : "memory");
  return m;
}
__device__ __forceinline__ bool elect_one() {
  uint32_t p;
  asm volatile("{.reg .pred p; elect.sync _|p, 0xffffffff; selp.u32 %0, 1, 0, p;}" : "=r"(p));
  return p != 0;
}
__device__ __forceinline__ int fresh_tid() { int v; asm volatile("mov.u32 %0, %%tid.x;" : "=r"(v)); return v; }
__device__ __forceinline__ int fresh_bid() { int v; asm volatile("mov.u32 %0, %%ctaid.x;" : "=r"(v)); return v; }
__device__ __forceinline__ void stsm2(uint32_t addr, uint32_t a, uint32_t b) {
  asm volatile("stmatrix.sync.aligned.m8n8.x2.shared.b16 [%0], {%1,%2};" ::"r"(addr), "r"(a), "r"(b) : "memory");
}
__device__ __forceinline__ uint4 lds128(uint32_t a) { uint4 v; asm volatile("ld.shared.v4.u32 {%0,%1,%2,%3}, [%4];" : "=r"(v.x), "=r"(v.y), "=r"(v.z), "=r"(v.w) : "r"(a) : "memory"); return v; }
__device__ __forceinline__ void stsm4(uint32_t addr, uint32_t a, uint32_t b, uint32_t c, uint32_t d) {
  asm volatile("stmatrix.sync.aligned.m8n8.x4.shared.b16 [%0], {%1,%2,%3,%4};" ::"r"(addr), "r"(a), "r"(b), "r"(c), "r"(d) : "memory");
}
__device__ __forceinline__ uint32_t pack_h(float lo, float hi) { uint32_t r; asm("cvt.rn.f16x2.f32 %0, %1, %2;" : "=r"(r) : "f"(hi), "f"(lo)); return r; }
__device__ __forceinline__ uint32_t pack_b(float lo, float hi) { uint32_t r; asm("cvt.rn.bf16x2.f32 %0, %1, %2;" : "=r"(r) : "f"(hi), "f"(lo)); return r; }
__device__ __forceinline__ float ex2f(float x) { float r; asm("ex2.approx.ftz.f32 %0, %1;" : "=f"(r) : "f"(x)); return r; }
__device__ __forceinline__ float bf_lo(uint32_t u) { return __uint_as_float(u << 16); }
__device__ __forceinline__ float bf_hi(uint32_t u) { return __uint_as_float(u & 0xffff0000u); }

#define F4(o) "+f"(d[o + 0]), "+f"(d[o + 1]), "+f"(d[o + 2]), "+f"(d[o + 3])
#define F8(o) F4(o), F4(o + 4)
#define F40(o) F8(o), F8(o + 8), F8(o + 16), F8(o + 24), F8(o + 32)
#define RU8(o) "+r"(d[o + 0]), "+r"(d[o + 1]), "+r"(d[o + 2]), "+r"(d[o + 3]), "+r"(d[o + 4]), "+r"(d[o + 5]), "+r"(d[o + 6]), "+r"(d[o + 7])
#define WU8(o) "=r"(d[o + 0]), "=r"(d[o + 1]), "=r"(d[o + 2]), "=r"(d[o + 3]), "=r"(d[o + 4]), "=r"(d[o + 5]), "=r"(d[o + 6]), "=r"(d[o + 7])
#define A4 "r"(a[0]), "r"(a[1]), "r"(a[2]), "r"(a[3])

__device__ __forceinline__ void mma_n128(float* d, uint64_t a, uint64_t b, int acc) {
  asm volatile(
      "{.reg .pred p; setp.ne.b32 p, %66, 0;\n"
      "wgmma.mma_async.sync.aligned.m64n128k16.f32.bf16.bf16 {"
      "%0,%1,%2,%3,%4,%5,%6,%7,%8,%9,%10,%11,%12,%13,%14,%15,%16,%17,%18,%19,%20,%21,%22,%23,"
      "%24,%25,%26,%27,%28,%29,%30,%31,%32,%33,%34,%35,%36,%37,%38,%39,%40,%41,%42,%43,%44,%45,%46,%47,"
      "%48,%49,%50,%51,%52,%53,%54,%55,%56,%57,%58,%59,%60,%61,%62,%63"
      "}, %64, %65, p, 1, 1, 0, 1;}"
      : F40(0), F8(40), F8(48), F8(56)
      : "l"(a), "l"(b), "r"(acc));
}
__device__ __forceinline__ void mma_n112(float* d, uint64_t a, uint64_t b, int acc) {
  asm volatile(
      "{.reg .pred p; setp.ne.b32 p, %58, 0;\n"
      "wgmma.mma_async.sync.aligned.m64n112k16.f32.bf16.bf16 {"
      "%0,%1,%2,%3,%4,%5,%6,%7,%8,%9,%10,%11,%12,%13,%14,%15,%16,%17,%18,%19,%20,%21,%22,%23,"
      "%24,%25,%26,%27,%28,%29,%30,%31,%32,%33,%34,%35,%36,%37,%38,%39,%40,%41,%42,%43,%44,%45,%46,%47,"
      "%48,%49,%50,%51,%52,%53,%54,%55"
      "}, %56, %57, p, 1, 1, 0, 1;}"
      : F40(0), F8(40), F8(48)
      : "l"(a), "l"(b), "r"(acc));
}
__device__ __forceinline__ void mma_n80(float* d, uint64_t a, uint64_t b, int acc) {
  asm volatile(
      "{.reg .pred p; setp.ne.b32 p, %42, 0;\n"
      "wgmma.mma_async.sync.aligned.m64n80k16.f32.bf16.bf16 {"
      "%0,%1,%2,%3,%4,%5,%6,%7,%8,%9,%10,%11,%12,%13,%14,%15,%16,%17,%18,%19,%20,%21,%22,%23,%24,%25,%26,%27,%28,%29,"
      "%30,%31,%32,%33,%34,%35,%36,%37,%38,%39}, %40, %41, p, 1, 1, 0, 1;}"
      : F40(0)
      : "l"(a), "l"(b), "r"(acc));
}
__device__ __forceinline__ void mma_qk_first(uint32_t* d, const uint32_t* a, uint64_t b) {
  asm volatile(
      "wgmma.mma_async.sync.aligned.m64n128k16.f16.f16.f16 {%0,%1,%2,%3,%4,%5,%6,%7,%8,%9,%10,%11,%12,%13,%14,%15,%16,%17,%18,%19,%20,%21,%22,%23,%24,%25,%26,%27,%28,%29,%30,%31}, {%32,%33,%34,%35}, %36, 0, 1, 1, 0;"
      : WU8(0), WU8(8), WU8(16), WU8(24)
      : A4, "l"(b));
}
__device__ __forceinline__ void mma_qk_acc(uint32_t* d, const uint32_t* a, uint64_t b) {
  asm volatile(
      "wgmma.mma_async.sync.aligned.m64n128k16.f16.f16.f16 {%0,%1,%2,%3,%4,%5,%6,%7,%8,%9,%10,%11,%12,%13,%14,%15,%16,%17,%18,%19,%20,%21,%22,%23,%24,%25,%26,%27,%28,%29,%30,%31}, {%32,%33,%34,%35}, %36, 1, 1, 1, 0;"
      : RU8(0), RU8(8), RU8(16), RU8(24)
      : A4, "l"(b));
}
__device__ __forceinline__ void mma_pv(uint32_t* d, const uint32_t* a, uint64_t b) {
  asm volatile("wgmma.mma_async.sync.aligned.m64n24k16.f16.f16.f16 {%0,%1,%2,%3,%4,%5}, {%6,%7,%8,%9}, %10, 1, 1, 1, 1;"
               : "+r"(d[0]), "+r"(d[1]), "+r"(d[2]), "+r"(d[3]), "+r"(d[4]), "+r"(d[5])
               : A4, "l"(b));
}
__device__ __forceinline__ void mma_b24_rs(float* d, const uint32_t* a, uint64_t b) {
  asm volatile("wgmma.mma_async.sync.aligned.m64n24k16.f32.bf16.bf16 {%0,%1,%2,%3,%4,%5,%6,%7,%8,%9,%10,%11}, {%12,%13,%14,%15}, %16, 1, 1, 1, 0;"
               : F4(0), F4(4), F4(8)
               : A4, "l"(b));
}
#define W4(o) "=f"(d[o + 0]), "=f"(d[o + 1]), "=f"(d[o + 2]), "=f"(d[o + 3])
__device__ __forceinline__ void mma_b24_rs0(float* d, const uint32_t* a, uint64_t b) {
  asm volatile("wgmma.mma_async.sync.aligned.m64n24k16.f32.bf16.bf16 {%0,%1,%2,%3,%4,%5,%6,%7,%8,%9,%10,%11}, {%12,%13,%14,%15}, %16, 0, 1, 1, 0;"
               : W4(0), W4(4), W4(8)
               : A4, "l"(b));
}
__device__ __forceinline__ void mma_b24_tt0(float* d, uint64_t a, uint64_t b) {
  asm volatile("wgmma.mma_async.sync.aligned.m64n24k16.f32.bf16.bf16 {%0,%1,%2,%3,%4,%5,%6,%7,%8,%9,%10,%11}, %12, %13, 0, 1, 1, 1, 1;"
               : W4(0), W4(4), W4(8)
               : "l"(a), "l"(b));
}
__device__ __forceinline__ void mma_b24_ss0(float* d, uint64_t a, uint64_t b) {
  asm volatile("wgmma.mma_async.sync.aligned.m64n24k16.f32.bf16.bf16 {%0,%1,%2,%3,%4,%5,%6,%7,%8,%9,%10,%11}, %12, %13, 0, 1, 1, 0, 0;"
               : W4(0), W4(4), W4(8)
               : "l"(a), "l"(b));
}
__device__ __forceinline__ void mma_b24_ss(float* d, uint64_t a, uint64_t b) {
  asm volatile("wgmma.mma_async.sync.aligned.m64n24k16.f32.bf16.bf16 {%0,%1,%2,%3,%4,%5,%6,%7,%8,%9,%10,%11}, %12, %13, 1, 1, 1, 0, 0;"
               : F4(0), F4(4), F4(8)
               : "l"(a), "l"(b));
}
__device__ __forceinline__ void mma_b24_tt(float* d, uint64_t a, uint64_t b) {
  asm volatile("wgmma.mma_async.sync.aligned.m64n24k16.f32.bf16.bf16 {%0,%1,%2,%3,%4,%5,%6,%7,%8,%9,%10,%11}, %12, %13, 1, 1, 1, 1, 1;"
               : F4(0), F4(4), F4(8)
               : "l"(a), "l"(b));
}

constexpr int G_XB = 16384, G_WB = 16384, G_PB = G_XB + 2 * G_WB;
constexpr int SM_STG = 3 * G_PB;
constexpr int SM_AK = 0;
constexpr int SM_AQ = 16 * KVB;
constexpr int SM_MISC = SM_STG + 12 * SLICE;
constexpr int SM_Q0 = 3 * KVB, SM_Q1 = 0;
constexpr int B_FULL = SM_MISC, B_EMPTY = B_FULL + 48, B_KV = B_EMPTY + 48, B_BD = B_KV + 256, B_AV = B_BD + 8, B_AQ = B_AV + 8,
              B_KD = B_AQ + 8, B_Q1 = B_KD + 8, B_QC = B_Q1 + 8, B_P2 = B_QC + 8, B_F1 = B_P2 + 8, B_AK = B_F1 + 8, B_A0 = B_AK + 8, B_QD = B_A0 + 8, B_OF = B_QD + 8,
              B_OE = B_OF + 64;
constexpr int SM_FLAG = SM_MISC + 640;
constexpr int SM_WPHI = SM_MISC + 768;
constexpr int SM_RED = SM_WPHI + 1536;
constexpr int SM_GATE = SM_RED + 256;
constexpr int SM_KVS = SM_GATE + 2048;
constexpr int SM_TOTAL = SM_KVS + 3840;
constexpr int O_AB = 16384, O_WB = 10240, O_STB = O_AB + O_WB;
__host__ __device__ constexpr int o_slot(int i) { return i < 5 ? SM_MISC - (5 - i) * O_STB : (i - 5) * O_STB; }

template <bool BR_B>
__device__ __forceinline__ void g_epilogue(float* acc, uint32_t stg, int ct, int w, int wp, int lane) {
  const int t = lane & 3, hf = (lane >> 3) & 1, csel = lane >> 4, r = lane & 7;
  const int Rw = w * 64 + wp * 16;
  const uint32_t offK = Rw * 16 + hf * 128 + r * 16, offV = (Rw / 8 + hf) * 384 + r * 16;
  const bool p0 = (PMASK >> (Rw / 8)) & 1, p1 = (PMASK >> (Rw / 8 + 1)) & 1;
  const bool lo = t < 2, ev = !(t & 1);
#pragma unroll
  for (int j = 0; j < 6; j++) {
    const int type = (ct * 12 + 2 * j) >> 5;
    float* a = acc + 20 * j;
    uint32_t aug0, aug1, q[10];
    if (BR_B) {
      const float s0 = type == 0 ? QSCALE : (type == 1 && p0) ? 0.001953125f : 1.f;
      const float s1 = type == 0 ? QSCALE : (type == 1 && p1) ? 0.001953125f : 1.f;
      aug0 = (type == 0 || !ev) ? 0u : (type == 1 && p0) ? 0x18001800u : 0x00003C00u;
      aug1 = (type == 0 || !ev) ? 0u : (type == 1 && p1) ? 0x18001800u : 0x00003C00u;
#pragma unroll
      for (int i = 0; i < 5; i++) { q[2 * i] = pack_h(a[4 * i] * s0, a[4 * i + 1] * s0); q[2 * i + 1] = pack_h(a[4 * i + 2] * s1, a[4 * i + 3] * s1); }
    } else {
      aug0 = aug1 = (type == 2 && ev) ? 0x00003F80u : 0u;
#pragma unroll
      for (int i = 0; i < 10; i++) q[i] = pack_b(a[2 * i], a[2 * i + 1]);
    }
    const uint32_t base = stg + 2 * j * SLICE + (type == 2 ? offV : offK);
    const uint32_t cs = type == 2 ? 128 : 2048;
    stsm4(base + csel * cs, q[0], q[1], q[2], q[3]);
    stsm4(base + 2 * cs + csel * SLICE, lo ? q[4] : aug0, lo ? q[5] : aug1, lo ? aug0 : q[4], lo ? aug1 : q[5]);
    stsm4(base + SLICE + csel * cs, q[6], q[7], q[8], q[9]);
  }
}

__device__ __forceinline__ uint32_t exp_mufu(uint32_t s) { uint32_t r; asm("ex2.approx.f16x2 %0, %1;" : "=r"(r) : "r"(s)); return r; }
__device__ __forceinline__ uint32_t hfma(uint32_t a, uint32_t b, uint32_t c) { uint32_t r; asm("fma.rn.f16x2 %0, %1, %2, %3;" : "=r"(r) : "r"(a), "r"(b), "r"(c)); return r; }
__device__ __forceinline__ uint32_t hfma_relu(uint32_t a, uint32_t b, uint32_t c) { uint32_t r; asm("fma.rn.relu.f16x2 %0, %1, %2, %3;" : "=r"(r) : "r"(a), "r"(b), "r"(c)); return r; }
#define D2(x) ((x) * 0x10001u)
__device__ __forceinline__ uint32_t exp_poly(uint32_t u, uint32_t zero) {
  uint32_t r = hfma_relu(u, D2(0x0200u), 0u);
  uint32_t f = hfma(r, D2(0xF800u), u);
  uint32_t w = hfma(f, D2(0x60fcu), D2(0x457fu));
  w = hfma(f, w, D2(0x27d8u));
  w = hfma_relu(f, w, D2(0x05a8u));
  return __funnelshift_l(zero, r, 10) + w;
}

__device__ __forceinline__ void phi_logits(float (*d)[12], uint32_t img16, uint32_t wphi16) {
  wg_fence();
#pragma unroll
  for (int tl = 0; tl < 2; tl++) {
    mma_b24_ss0(d[tl], mkdesc(img16 + tl * 64, 2048, 128, 0), mkdesc(wphi16, 384, 128, 0));
    mma_b24_ss(d[tl], mkdesc(img16 + tl * 64 + 128, 2048, 128, 0), mkdesc(wphi16 + 48, 384, 128, 0));
  }
  wg_commit();
  wg_wait<0>();
  fence_f<12>(d[0]); fence_f<12>(d[1]);
}
__device__ __forceinline__ void feature_map2(uint32_t (*ph)[10], uint32_t img16, int t, uint32_t wphi16) {
  float d[2][12];
  phi_logits(d, img16, wphi16);
  const bool lo = t < 2;
  float am = 0.f;
#pragma unroll
  for (int i = 0; i < 12; i++) {
    d[0][i] *= 1.4426950408889634f; d[1][i] *= 1.4426950408889634f;
    am = fmaxf(am, fmaxf(fabsf(d[0][i]), fabsf(d[1][i])));
  }
  if (!__all_sync(~0u, am <= 60.f)) {
#pragma unroll
    for (int tl = 0; tl < 2; tl++)
#pragma unroll
      for (int hf = 0; hf < 2; hf++) {
        float* x = d[tl] + 2 * hf;
        float mx = fmaxf(fmaxf(fmaxf(x[0], x[1]), fmaxf(x[4], x[5])), fmaxf(x[8], x[9]));
        float mn = fminf(fminf(fminf(x[0], x[1]), fminf(x[4], x[5])), fminf(x[8], x[9]));
        mx = fmaxf(mx, __shfl_xor_sync(~0u, mx, 1)); mn = fminf(mn, __shfl_xor_sync(~0u, mn, 1));
        mx = fmaxf(mx, __shfl_xor_sync(~0u, mx, 2)); mn = fminf(mn, __shfl_xor_sync(~0u, mn, 2));
        const float p0 = ex2f(x[0] - mx), p1 = ex2f(x[1] - mx), p2 = ex2f(x[4] - mx), p3 = ex2f(x[5] - mx);
        const float n0 = ex2f(mn - x[0]), n1 = ex2f(mn - x[1]), n2 = ex2f(mn - x[4]), n3 = ex2f(mn - x[5]);
        const float m0 = ex2f(lo ? x[8] - mx : mn - x[8]), m1 = ex2f(lo ? x[9] - mx : mn - x[9]), ms = m0 + m1;
        float sp = (p0 + p1) + (p2 + p3) + (lo ? ms : 0.f), sn = (n0 + n1) + (n2 + n3) + (lo ? 0.f : ms);
        sp += __shfl_xor_sync(~0u, sp, 1); sn += __shfl_xor_sync(~0u, sn, 1);
        sp += __shfl_xor_sync(~0u, sp, 2); sn += __shfl_xor_sync(~0u, sn, 2);
        const float rp = __fdividef(1.f, sp), rn = __fdividef(1.f, sn), rm = lo ? rp : rn;
        ph[tl][hf] = pack_b(p0 * rp, p1 * rp); ph[tl][2 + hf] = pack_b(p2 * rp, p3 * rp); ph[tl][4 + hf] = pack_b(m0 * rm, m1 * rm);
        ph[tl][6 + hf] = pack_b(n0 * rn, n1 * rn); ph[tl][8 + hf] = pack_b(n2 * rn, n3 * rn);
      }
    return;
  }
  const uint32_t sgn = lo ? 0u : 0x80000000u;
#pragma unroll
  for (int tl = 0; tl < 2; tl++)
#pragma unroll
    for (int hf = 0; hf < 2; hf++) {
      const float* x = d[tl] + 2 * hf;
      const float p0 = ex2f(x[0]), p1 = ex2f(x[1]), p2 = ex2f(x[4]), p3 = ex2f(x[5]);
      const float n0 = ex2f(-x[0]), n1 = ex2f(-x[1]), n2 = ex2f(-x[4]), n3 = ex2f(-x[5]);
      const float m0 = ex2f(__uint_as_float(__float_as_uint(x[8]) ^ sgn)), m1 = ex2f(__uint_as_float(__float_as_uint(x[9]) ^ sgn)), ms = m0 + m1;
      float sp = (p0 + p1) + (p2 + p3), sn = (n0 + n1) + (n2 + n3);
      if (lo) sp += ms; else sn += ms;
      sp += __shfl_xor_sync(~0u, sp, 1); sn += __shfl_xor_sync(~0u, sn, 1);
      sp += __shfl_xor_sync(~0u, sp, 2); sn += __shfl_xor_sync(~0u, sn, 2);
      const float rp = __fdividef(1.f, sp), rn = __fdividef(1.f, sn), rm = lo ? rp : rn;
      ph[tl][hf] = pack_b(p0 * rp, p1 * rp); ph[tl][2 + hf] = pack_b(p2 * rp, p3 * rp); ph[tl][4 + hf] = pack_b(m0 * rm, m1 * rm);
      ph[tl][6 + hf] = pack_b(n0 * rn, n1 * rn); ph[tl][8 + hf] = pack_b(n2 * rn, n3 * rn);
    }
}

__device__ __forceinline__ void store_o(const float* o, float r0, float r1, int cbase, int h, int row, int t) {
  uint32_t* p = (uint32_t*)(g_o + ((size_t)(row >> 7) * 160 + cbase + (h >> 1) * 5) * 2048 + (row & 127) * 16) + t;
  const int c0 = (h & 1) ? 3 : 0;
  p[c0 * 512] = pack_b(o[0] * r0, o[1] * r0); p[c0 * 512 + 32] = pack_b(o[2] * r1, o[3] * r1);
  p[c0 * 512 + 512] = pack_b(o[4] * r0, o[5] * r0); p[c0 * 512 + 544] = pack_b(o[6] * r1, o[7] * r1);
  if ((t >> 1) == (h & 1)) { p[1024] = pack_b(o[8] * r0, o[9] * r0); p[1056] = pack_b(o[10] * r1, o[11] * r1); }
}

__device__ __noinline__ void attn_fallback(const uint32_t* flags, int h, int part, const __nv_bfloat16* x, const __nv_bfloat16* wB) {
  __nv_bfloat16* kv = g_fb + (size_t)h * S_ * 40;
  const int tid = threadIdx.x;
  for (int i = tid; i < S_ * 40; i += 512) {
    const int tok = i / 40, c = i % 40;
    const __nv_bfloat16* xr = x + (size_t)tok * D_;
    const __nv_bfloat16* wc = wB + (c < 20 ? 640 + h * 20 + c : 1280 + h * 20 + c - 20);
    float acc = 0.f;
    for (int k = 0; k < D_; k++) acc += __bfloat162float(xr[k]) * __bfloat162float(wc[(size_t)k * 1920]);
    kv[i] = __float2bfloat16(acc);
  }
  bar_sync(8, 512);
  const int warp = tid >> 5, lane = tid & 31;
  for (int wt = warp; wt < 32; wt += 16) {
    if (!flags[wt]) continue;
    for (int rr = 0; rr < 16; rr++) {
      const int row = part * 512 + wt * 16 + rr;
      float qv = 0.f;
      if (lane < 20) {
        for (int k = 0; k < D_; k++) qv += __bfloat162float(x[(size_t)row * D_ + k]) * __bfloat162float(wB[(size_t)k * 1920 + h * 20 + lane]);
        qv = __bfloat162float(__float2bfloat16(qv)) * QSCALE;
      }
      float m = -INFINITY, l = 0.f, o[20];
#pragma unroll
      for (int d = 0; d < 20; d++) o[d] = 0.f;
      for (int j = lane; j < S_; j += 32) {
        float s = 0.f;
#pragma unroll
        for (int d = 0; d < 20; d++) s += __shfl_sync(~0u, qv, d) * __bfloat162float(kv[j * 40 + d]);
        const float mn = fmaxf(m, s), c = exp2f(m - mn), p = exp2f(s - mn);
        l = l * c + p;
#pragma unroll
        for (int d = 0; d < 20; d++) o[d] = o[d] * c + p * __bfloat162float(kv[j * 40 + 20 + d]);
        m = mn;
      }
      float mg = m;
#pragma unroll
      for (int of = 16; of; of >>= 1) mg = fmaxf(mg, __shfl_xor_sync(~0u, mg, of));
      const float c = exp2f(m - mg);
      l *= c;
#pragma unroll
      for (int of = 16; of; of >>= 1) l += __shfl_xor_sync(~0u, l, of);
      const float sc = (1.f - __ldcg(g_gate + row)) / l;
#pragma unroll
      for (int d = 0; d < 20; d++) {
        float v = o[d] * c;
#pragma unroll
        for (int of = 16; of; of >>= 1) v += __shfl_xor_sync(~0u, v, of);
        const int col = h * 20 + d;
        if (lane == 0) *(__nv_bfloat16*)(g_o + ((size_t)(row >> 7) * 160 + 80 + (col >> 3)) * 2048 + (row & 127) * 16 + (col & 7) * 2) = __float2bfloat16(v * sc);
      }
    }
  }
  bar_sync(8, 512);
}

__device__ __forceinline__ void load_q(uint32_t* qa, uint8_t* sm, int img, int tile) {
  const int tid = fresh_tid(), t = tid & 3, odd = (fresh_bid() >> 2) & 1;
  const uint32_t st = ((const uint32_t*)(sm + SM_RED))[tid & 31];
  const uint32_t* qp = (const uint32_t*)(sm + img + (tid >> 7) * 3072) + (((tid >> 5) & 3) * 16 + ((tid & 31) >> 2)) * 4;
  qa[0] = qp[t]; qa[1] = qp[32 + t]; qa[2] = qp[256 + t]; qa[3] = qp[288 + t]; qa[6] = qp[512 + t]; qa[7] = qp[544 + t];
  qa[4] = qa[5] = qp[512 + (odd ? 1 : 3)];
  const float kn2 = __uint_as_float(__reduce_max_sync(~0u, (tid & 16) ? 0u : st)), vmx = __uint_as_float(__reduce_max_sync(~0u, (tid & 16) ? st : 0u));
  float n0 = 0.f, n1 = 0.f;
#pragma unroll
  for (int c = 0; c < 4; c++) {
    if (c == 2) continue;
    const float2 a = __half22float2(*(__half2*)&qa[2 * c]), b = __half22float2(*(__half2*)&qa[2 * c + 1]);
    n0 += a.x * a.x + a.y * a.y; n1 += b.x * b.x + b.y * b.y;
  }
  n0 += __shfl_xor_sync(~0u, n0, 1); n1 += __shfl_xor_sync(~0u, n1, 1);
  n0 += __shfl_xor_sync(~0u, n0, 2); n1 += __shfl_xor_sync(~0u, n1, 2);
  float r0, r1;
  asm("sqrt.approx.f32 %0, %1;" : "=f"(r0) : "f"(n0 * kn2));
  asm("sqrt.approx.f32 %0, %1;" : "=f"(r1) : "f"(n1 * kn2));
  const float b0 = r0 * 1.01f + 0.05f, b1 = r1 * 1.01f + 0.05f;
  const float m0 = fmaxf(0.f, ceilf(b0) - 15.f), m1 = fmaxf(0.f, ceilf(b1) - 15.f);
  if (t == (odd ? 0 : 2)) { qa[6] = pack_h(-m0, 13.5f); qa[7] = pack_h(-m1, 13.5f); }
  const bool ok = b0 <= 30.f && b1 <= 30.f && n0 <= 1048576.f && n1 <= 1048576.f && kn2 <= 1048576.f && vmx <= 32768.f && vmx >= 0.00390625f;
  if (!ok) ((volatile uint32_t*)(sm + SM_FLAG))[(tid >> 7) * 8 + tile * 4 + ((tid >> 5) & 3)] = 1;
  __syncwarp();
}

struct Params {
  CUtensorMap tmX, tmWB, tmWA, tmOut;
  const __nv_bfloat16 *x, *gate_w, *w_phi, *wB, *woA, *woB;
};

__device__ __forceinline__ void agent(const Params& P, uint32_t sb) {
  const int bid = blockIdx.x, rank = bid & 1, lane = threadIdx.x & 31;
  const int pr = bid >> 1, rt = (pr & 7) * 2 + rank, ct = pr >> 3, h = bid >> 2, part = bid & 3;
  if (elect_one()) {
#pragma unroll
    for (int it = 0; it < 6; it += 2) {
      const int s = (it + 2) % 6;
      mbar_expect_tx(sb + B_FULL + 8 * s, G_XB + G_WB);
      mbar_expect_tx(sb + B_FULL + 8 * s + 8, G_WB);
      tma2d(sb + (s >> 1) * G_PB, &P.tmX, it * 32, rt * 128, sb + B_FULL + 8 * s);
    }
  }
  asm volatile("barrier.cluster.wait.aligned;" ::: "memory");
  if (elect_one()) {
#pragma unroll
    for (int it = 0; it < 6; it++) {
      const int s = (it + 2) % 6;
      const uint32_t st = sb + (s >> 1) * G_PB + G_XB + (s & 1) * G_WB + rank * 8192, fb = sb + B_FULL + 8 * s;
      tma2d_mc(st, &P.tmWB, ct * 240 + rank * 128, it * 32, fb, 3);
      tma2d_mc(st + 4096, &P.tmWB, ct * 240 + rank * 128 + 64, it * 32, fb, 3);
    }
    asm volatile("prefetch.tensormap [%0];" ::"l"(&P.tmWA) : "memory");
  }
  {
    int s = 2, ph = 0;
#pragma unroll 1
    for (int it = 6; it < 40; it++) {
      const int kb = it >= 20 ? it - 20 : it;
      const uint32_t st = sb + (s >> 1) * G_PB + G_XB + (s & 1) * G_WB + rank * 8192, fb = sb + B_FULL + 8 * s;
      const CUtensorMap* wm = it >= 20 ? &P.tmWA : &P.tmWB;
      mbar_wait_z(sb + B_EMPTY + 8 * s, ph);
      if (elect_one()) {
        mbar_expect_tx(fb, (s & 1) ? G_WB : G_XB + G_WB);
        if (s & 1) tma2d(sb + (s >> 1) * G_PB, &P.tmX, (kb - 1) * 32, rt * 128, fb - 8);
        tma2d_mc(st, wm, ct * 240 + rank * 128, kb * 32, fb, 3);
        tma2d_mc(st + 4096, wm, ct * 240 + rank * 128 + 64, kb * 32, fb, 3);
      }
      if (s == 1) ph ^= 1;
      if (++s == 6) s = 0;
    }
  }
  const uint8_t* kvsrc = g_kvB + (size_t)h * 16 * KVB;
  const uint8_t* qsrc = g_qB + ((size_t)h * 16 + part * 4) * SLICE;
  await(C_B, 128);
  if (lane == 0) TS(0, 11);
  mbar_wait_z(sb + B_EMPTY + 8, 1);
  if (elect_one()) {
    fence_async_g();
    mbar_expect_tx(sb + B_BD, 2 * SLICE + 2048 + 128);
#pragma unroll
    for (int q = 0; q < 12; q++) bulk_g2s(sb + SM_Q0 + q * 1024, qsrc + q * 2048, 1024, sb + B_BD);
    bulk_g2s(sb + SM_RED, g_stat + h * 32, 128, sb + B_BD);
    bulk_g2s(sb + SM_GATE, g_gate + part * 512, 2048, sb + B_BD);
#pragma unroll
    for (int j = 0; j < 3; j++) { mbar_expect_tx(sb + B_KV + 8 * j, KVB); bulk_g2s(sb + j * KVB, kvsrc + j * KVB, KVB, sb + B_KV + 8 * j); }
  }
#pragma unroll
  for (int q = 1; q < 3; q++) {
    mbar_wait_z(sb + B_EMPTY + 16 * q + 8, 0);
    if (elect_one()) {
#pragma unroll
      for (int j = 4 * q; j < 4 * q + 4; j++) { mbar_expect_tx(sb + B_KV + 8 * j, KVB); bulk_g2s(sb + j * KVB, kvsrc + j * KVB, KVB, sb + B_KV + 8 * j); }
    }
  }
  bar_sync(9, 288);
  if (lane == 0) TS(0, 12);
  if (lane == 0) {
#pragma unroll
    for (int q = 0; q < 12; q++) bulk_s2g(g_A + ((size_t)(ct * 12 + q) * 16 + rt) * SLICE, sb + SM_STG + q * SLICE, SLICE);
    bulk_commit();
  }
  __syncwarp();
  mbar_wait_z(sb + B_QC, 0);
  if (lane == 0) TS(0, 13);
  if (elect_one()) { mbar_expect_tx(sb + B_KV + 24, KVB); bulk_g2s(sb + 3 * KVB, kvsrc + 3 * KVB, KVB, sb + B_KV + 24); }
  if (lane == 0) { bulk_wait_all(); signal(C_A + bid * 8); }
  __syncwarp();
  if (lane == 0) TS(0, 14);
  if (elect_one()) {
#pragma unroll
    for (int j = 12; j < 16; j++) { mbar_expect_tx(sb + B_KV + 8 * j, KVB); bulk_g2s(sb + j * KVB, kvsrc + j * KVB, KVB, sb + B_KV + 8 * j); }
  }
  {
    const int l12 = lane % 12, c2 = ((l12 >> 2) * 32 + h) / 12, r2 = part * 4 + (l12 & 3);
    await_all(C_A + (((c2 * 8 + (r2 >> 1)) << 1) | (r2 & 1)) * 8, 1);
  }
  if (lane == 0) TS(0, 15);
  mbar_wait_z(sb + B_P2, 0);
  if (lane == 0) TS(0, 16);
  if (elect_one()) {
    fence_async_g();
    mbar_expect_tx(sb + B_AV, 8 * SLICE);
#pragma unroll
    for (int q = 0; q < 4; q++) {
      bulk_g2s(sb + SM_AK + q * 16384 + SLICE, g_A + ((size_t)(H_ + h) * 16 + part * 4 + q) * SLICE, SLICE, sb + B_AV);
      bulk_g2s(sb + SM_AK + q * 16384, g_A + ((size_t)(2 * H_ + h) * 16 + part * 4 + q) * SLICE, SLICE, sb + B_AV);
    }
    mbar_expect_tx(sb + B_AQ, 4 * SLICE);
    bulk_g2s(sb + SM_AQ, g_A + ((size_t)h * 16 + part * 4) * SLICE, 4 * SLICE, sb + B_AQ);
  }
  mbar_wait_z(sb + B_A0, 0);
  if (elect_one()) {
    mbar_expect_tx(sb + B_Q1, 2 * SLICE);
#pragma unroll
    for (int q = 0; q < 12; q++) bulk_g2s(sb + SM_Q1 + q * 1024, qsrc + q * 2048 + 1024, 1024, sb + B_Q1);
  }
  mbar_wait_z(sb + B_AK, 0);
  if (lane == 0) TS(0, 17);
  if (lane == 0) signal(C_KV + h * 32);
  await(C_KV + h * 32, 4);
  if (lane == 0) TS(0, 18);
  if (elect_one()) {
    fence_async_g();
    mbar_expect_tx(sb + B_KD, 3840);
    bulk_g2s(sb + SM_KVS, g_kvs + h * 960, 3840, sb + B_KD);
  }
  mbar_wait_z(sb + B_QC, 1);
  if (elect_one()) {
#pragma unroll
    for (int j = 5; j >= 0; j--) { mbar_expect_tx(sb + B_KV + 248 - 8 * j, KVB); bulk_g2s(sb + j * KVB, kvsrc + j * KVB, KVB, sb + B_KV + 248 - 8 * j); }
  }
  mbar_wait_z(sb + B_QD, 0);
  if (lane == 0) TS(0, 19);
  if (lane == 0) signal(C_OA + part * 32);
  const uint8_t* osrc = g_o + (size_t)(bid >> 3) * 160 * 2048;
  const uint8_t* wsrc = g_wo + (bid & 7) * 204800;
  await(C_OA + (bid >> 5) * 32, 32);
  if (lane == 0) TS(0, 20);
  mbar_wait_z(sb + B_F1, 0);
  if (lane == 0) TS(0, 21);
  if (elect_one()) {
    fence_async_g();
#pragma unroll
    for (int it = 0; it < 5; it++) {
      mbar_expect_tx(sb + B_OF + 8 * it, O_STB);
      bulk_g2s(sb + o_slot(it) + O_AB, wsrc + it * O_WB, O_WB, sb + B_OF + 8 * it);
      bulk_g2s(sb + o_slot(it), osrc + it * O_AB, O_AB, sb + B_OF + 8 * it);
    }
  }
  bar_sync(10, 64);
  if (elect_one()) {
#pragma unroll
    for (int it = 5; it < 8; it++) {
      mbar_expect_tx(sb + B_OF + 8 * it, O_STB);
      bulk_g2s(sb + o_slot(it) + O_AB, wsrc + it * O_WB, O_WB, sb + B_OF + 8 * it);
      bulk_g2s(sb + o_slot(it), osrc + it * O_AB, O_AB, sb + B_OF + 8 * it);
    }
  }
#pragma unroll
  for (int it = 8; it < NPRE; it++) {
    const uint32_t st = sb + o_slot(it & 7), fb = sb + B_OF + 8 * (it & 7);
    mbar_wait(sb + B_OE + 8 * (it & 7), it >> 4);
    if (elect_one()) {
      mbar_expect_tx(fb, O_STB);
      if (it < 10) bulk_g2s_mc(st + rank * 8192, osrc + it * O_AB + rank * 8192, 8192, fb, 3);
      bulk_g2s(st + O_AB, wsrc + it * O_WB, O_WB, fb);
    }
  }
  const int ob = C_OB + (bid >> 5) * 8 + lane * 32;
  uint32_t ready = 0;
#pragma unroll
  for (int it = 10; it < 20; it++) {
    const uint32_t st = sb + o_slot(it & 7), fb = sb + B_OF + 8 * (it & 7);
    const int h0 = (it - 10) * 64 / 20, h1 = ((it - 10) * 64 + 63) / 20;
    const uint32_t need = (uint32_t)((2ull << h1) - (1ull << h0));
    if (it >= NPRE) {
      mbar_wait(sb + B_OE + 8 * (it & 7), it >> 4);
      if (elect_one()) { mbar_expect_tx(fb, O_STB); bulk_g2s(st + O_AB, wsrc + it * O_WB, O_WB, fb); }
    }
    if ((ready & need) != need) { ready = await_mask(ob, need); fence_async_g(); }
    if (elect_one()) {
      if (it == 10) TS(2, 1);
      bulk_g2s_mc(st + rank * 8192, osrc + it * O_AB + rank * 8192, 8192, fb, 3);
    }
  }
  uint32_t v = 0;
  if (lane == 0) v = atomicAdd(&g_cnt[C_EXIT], 1u);
  if (__shfl_sync(~0u, v, 0) == 127u) {
    g_cnt[C_KV + 32 * lane] = 0;
    if (lane < 7) g_cnt[32 * lane] = 0;
#pragma unroll
    for (int i = 0; i < 4; i++) { g_cnt[C_A + 8 * (lane + 32 * i)] = 0; g_cnt[C_OB + 8 * (lane + 32 * i)] = 0; }
  }
}

__global__ void __cluster_dims__(2, 1, 1) __launch_bounds__(640, 1) fused_kernel(const __grid_constant__ Params P) {
  extern __shared__ __align__(1024) uint8_t sm[];
  const uint32_t sb = __shfl_sync(~0u, smem_u32(sm), 0), sl = sb & 0x3FFFF;
  const int tid = threadIdx.x, wg = __shfl_sync(~0u, tid >> 7, 0), wp = __shfl_sync(~0u, (tid >> 5) & 3, 0), lane = tid & 31;
  const int bid = blockIdx.x;
  if (wg == 4 && wp == 0) {
    if (elect_one()) {
      TS(0, 0);
      asm volatile("prefetch.tensormap [%0];" ::"l"(&P.tmX) : "memory");
      asm volatile("prefetch.tensormap [%0];" ::"l"(&P.tmWB) : "memory");
#pragma unroll
      for (int i = 0; i < 6; i++) { mbar_init(sb + B_FULL + 8 * i, 1); mbar_init(sb + B_EMPTY + 8 * i, 4); }
      mbar_init(sb + B_BD, 1);
    }
  }
  TQ(32);
  __syncthreads();
  asm volatile("barrier.cluster.arrive.release.aligned;" ::: "memory");
  if (wg == 4) {
    asm volatile("setmaxnreg.dec.sync.aligned.u32 32;");
    if (wp == 0) agent(P, sb);
    else asm volatile("barrier.cluster.wait.aligned;" ::: "memory");
    cluster_sync();
    return;
  }
  asm volatile("barrier.cluster.wait.aligned;" ::: "memory");
  {
    const int pr = bid >> 1, rt = (pr & 7) * 2 + (bid & 1), ct = pr >> 3;
    const int h = bid >> 2, part = bid & 3, odd = h & 1;
    const uint32_t stg = sb + SM_STG;
    if (wg < 2) {
      asm volatile("setmaxnreg.inc.sync.aligned.u32 168;");
      float acc[120];
      int s = 2, ph = 0;
#pragma unroll 1
      for (int round = 0; round < 2; round++) {
        int prev = 0;
#pragma unroll 1
        for (int kb = 0; kb < 20; kb++) {
          mbar_wait(sb + B_FULL + 8 * s, ph);
          if (tid == 0 && kb == 0) TS(0, 1 + round * 5);
          const uint32_t xa = (sl + (s >> 1) * G_PB + wg * 8192 + (s & 1) * 64) >> 4, wa = (sl + (s >> 1) * G_PB + G_XB + (s & 1) * G_WB) >> 4;
          wg_fence();
#pragma unroll
          for (int k = 0; k < 2; k++) {
            mma_n128(acc, mkdesc(xa + 2 * k, 16, 1024, 1), mkdesc(wa + 128 * k, 4096, 1024, 1), (kb | k) != 0);
            mma_n112(acc + 64, mkdesc(xa + 2 * k, 16, 1024, 1), mkdesc(wa + 512 + 128 * k, 4096, 1024, 1), (kb | k) != 0);
          }
          wg_commit();
          if (kb > 0) {
            wg_wait<1>();
            if ((tid & 127) < 2) mbar_arrive_cluster(sb + B_EMPTY + 8 * prev, tid & 1);
          }
          prev = s;
          if (s == 1) ph ^= 1;
          if (++s == 6) s = 0;
        }
        wg_wait<0>();
        fence_f<120>(acc);
        if (tid == 0) TS(0, 3 + round * 5);
        if ((tid & 127) < 2) mbar_arrive_cluster(sb + B_EMPTY + 8 * prev, tid & 1);
        if (round == 0) {
          g_epilogue<true>(acc, stg, ct, wg, wp, lane);
          fence_async();
          bar_arrive(1, 416);
        } else {
          bar_sync(2, 416);
          g_epilogue<false>(acc, stg, ct, wg, wp, lane);
          fence_async();
          bar_arrive(9, 288);
        }
        if (tid == 0) TS(0, 4 + round * 5);
      }
      asm volatile("setmaxnreg.dec.sync.aligned.u32 112;");
    } else {
      asm volatile("setmaxnreg.dec.sync.aligned.u32 56;");
      if (wg == 3) {
        const int t7 = tid & 127;
        if (wp == 0 && elect_one()) {
#pragma unroll
          for (int i = 0; i < 32; i++) mbar_init(sb + B_KV + 8 * i, 1);
#pragma unroll
          for (int i = 16; i < 26; i++) mbar_arrive(sb + B_KV + 8 * i);
          mbar_init(sb + B_AV, 1); mbar_init(sb + B_AQ, 1); mbar_init(sb + B_KD, 1); mbar_init(sb + B_Q1, 1);
          mbar_init(sb + B_QC, 16); mbar_init(sb + B_P2, 16); mbar_init(sb + B_F1, 16); mbar_init(sb + B_AK, 16); mbar_init(sb + B_A0, 4); mbar_init(sb + B_QD, 4);
#pragma unroll
          for (int i = 0; i < 8; i++) { mbar_init(sb + B_OF + 8 * i, 1); mbar_init(sb + B_OE + 8 * i, 4); }
          asm volatile("fence.mbarrier_init.release.cluster;" ::: "memory");
        }
        if (t7 < 32) ((uint32_t*)(sm + SM_FLAG))[t7] = 0;
        if (part == 0) for (int i = t7; i < 240; i += 128) ((float4*)g_kvs)[h * 240 + i] = make_float4(0.f, 0.f, 0.f, 0.f);
#pragma unroll
        for (int u = 0; u < 6; u++) {
          const int i = t7 + 128 * u, kc = i / 192, f = (i % 192) >> 3, pos = (kc == 3 ? 2 : kc) * 8 + (i & 7);
          const int d = kc == 2 ? -1 : odd ? (pos < 16 ? pos + 4 : pos - 20) : (pos < 20 ? pos : -1);
          const __nv_bfloat16 w = d >= 0 ? P.w_phi[h * 400 + d * 20 + (f < 20 ? f : f - 4)] : __float2bfloat16(0.f);
          ((__nv_bfloat16*)(sm + SM_WPHI))[i] = w;
        }
        fence_async();
        {
          uint4 gw[3];
#pragma unroll
          for (int i = 0; i < 3; i++) gw[i] = (lane + 32 * i < 80) ? ((const uint4*)P.gate_w)[lane + 32 * i] : make_uint4(0, 0, 0, 0);
#pragma unroll 2
          for (int rr = 0; rr < 4; rr++) {
            const int row = bid * 16 + wp * 4 + rr;
            float z = 0.f;
#pragma unroll
            for (int i = 0; i < 3; i++) {
              if (lane + 32 * i < 80) {
                const uint4 xv = ((const uint4*)(P.x + (size_t)row * D_))[lane + 32 * i];
                z += bf_lo(xv.x) * bf_lo(gw[i].x) + bf_hi(xv.x) * bf_hi(gw[i].x) + bf_lo(xv.y) * bf_lo(gw[i].y) + bf_hi(xv.y) * bf_hi(gw[i].y);
                z += bf_lo(xv.z) * bf_lo(gw[i].z) + bf_hi(xv.z) * bf_hi(gw[i].z) + bf_lo(xv.w) * bf_lo(gw[i].w) + bf_hi(xv.w) * bf_hi(gw[i].w);
              }
            }
#pragma unroll
            for (int o = 16; o; o >>= 1) z += __shfl_xor_sync(~0u, z, o);
            if (lane == 0) g_gate[row] = 1.f / (1.f + __expf(-z));
          }
        }
        bar_sync(1, 416);
        const bool pl = (PMASK >> (t7 >> 3)) & 1;
#pragma unroll 2
        for (int q = 0; q < 12; q++) {
          const int sidx = ct * 12 + q, type = sidx >> 5;
          if (type == 0) continue;
          const uint32_t ad = stg + q * SLICE + (type == 1 ? t7 * 16 : (t7 >> 3) * 384 + (t7 & 7) * 16), cs = type == 1 ? 2048 : 128;
          const uint4 c0 = lds128(ad), c1 = lds128(ad + cs), c2 = lds128(ad + 2 * cs);
          const uint32_t v[10] = {c0.x, c0.y, c0.z, c0.w, c1.x, c1.y, c1.z, c1.w, (q & 1) ? c2.z : c2.x, (q & 1) ? c2.w : c2.y};
          float r;
          if (type == 1) {
            float r1 = 0.f;
            r = 0.f;
#pragma unroll
            for (int i = 0; i < 10; i++) { const float2 f = __half22float2(*(const __half2*)&v[i]); r = fmaf(f.x, f.x, r); r1 = fmaf(f.y, f.y, r1); }
            r += r1;
            if (pl) r *= 262144.f;
          } else {
            uint32_t m = 0;
#pragma unroll
            for (int i = 0; i < 10; i++) m = __vmaxu2(m, v[i] & 0x7fff7fffu);
            m = max(m & 0xffffu, m >> 16);
            r = __half2float(__ushort_as_half((unsigned short)m));
          }
          const uint32_t u = __reduce_max_sync(~0u, __float_as_uint(r));
          if (lane == 0) ((uint32_t*)(sm + SM_RED))[q * 4 + wp] = u;
        }
        bar_arrive(2, 416);
        bar_sync(7, 128);
        if (t7 < 12) {
          const int sidx = ct * 12 + t7, type = sidx >> 5, head = sidx & 31;
          const uint4 u = *(const uint4*)(sm + SM_RED + t7 * 16);
          if (type != 0) g_stat[head * 32 + (type - 1) * 16 + rt] = __uint_as_float(max(max(u.x, u.y), max(u.z, u.w)));
        }
        fence_async();
        bar_arrive(3, 256);
      } else if (wp == 1) {
        bar_sync(1, 416);
        if (lane == 0) {
#pragma unroll 1
          for (int q = 0; q < 12; q++) {
            const int sidx = ct * 12 + q, type = sidx >> 5, head = sidx & 31;
            bulk_s2g(type == 0 ? g_qB + ((size_t)head * 16 + rt) * SLICE : g_kvB + ((size_t)head * 16 + rt) * KVB + (type - 1) * SLICE, stg + q * SLICE, SLICE);
          }
          bulk_commit();
          bulk_wait_all();
        }
        __syncwarp();
        bar_arrive(2, 416);
        bar_sync(3, 256);
        if (lane == 0) { signal(C_B); TS(0, 10); }
        __syncwarp();
      } else {
        const int i0 = (wp == 0 ? 0 : wp - 1) * 32 + lane;
#pragma unroll 1
        for (int b = 0; b < 2; b++) {
          uint4 v[5];
#pragma unroll
          for (int u = 0; u < 5; u++) {
            const int i = min(i0 + 96 * (5 * b + u), 799), c = bid * 100 + (i >> 3), k = (c / 80) * 8 + (i & 7);
            v[u] = __ldg((const uint4*)(k < 640 ? P.woA + k * 640 : P.woB + (k - 640) * 640) + c % 80);
          }
#pragma unroll
          for (int u = 0; u < 5; u++) {
            const int i = min(i0 + 96 * (5 * b + u), 799), c = bid * 100 + (i >> 3), pc = c % 80;
            *(uint4*)(g_wo + (size_t)(pc / 10) * 204800 + (c / 80) * 1280 + (pc % 10) * 128 + (i & 7) * 16) = v[u];
          }
        }
        bar_arrive(3, 256);
      }
      asm volatile("setmaxnreg.inc.sync.aligned.u32 112;");
    }
  }
  if (lane == 0 && wp == 0) TS(1, wg);
  TQ(35);
  uint32_t qa[8], oh[6], s[32], p[32];
  float o[12];
  mbar_wait(sb + B_BD, 0);
  load_q(qa, sm, SM_Q0, 0);
  if (elect_one()) mbar_arrive(sb + B_QC);
#pragma unroll
  for (int i = 0; i < 12; i++) o[i] = 0.f;
  fence_u<8>(qa);
  if (lane == 0 && wp == 0) TS(1, 4 + wg);
  TQ(34);
  const uint32_t stops = wg < 2 ? STOPS0 : STOPS1;
#pragma unroll 1
  for (int j0 = 0; j0 < 16;) {
    const int nit = __ffs(stops >> j0), jj = j0 + nit - 1;
    uint32_t bar = sb + B_KV + 16 * j0;
    const uint32_t k16 = (sl + (j0 < 8 ? 2 * j0 : 31 - 2 * j0) * KVB) >> 4;
    uint64_t dk0 = mkdesc(k16, 2048, 128, 0), dk1 = mkdesc(k16 + 128, 2048, 128, 0), dv[8];
#pragma unroll
    for (int i = 0; i < 8; i++) dv[i] = mkdesc(k16 + ((SLICE + i * 768) >> 4), 384, 128, 0);
#pragma unroll
    for (int i = 0; i < 6; i++) oh[i] = 0;
    fence_u<6>(oh);
    const int jodd = j0 & 1;
    const uint32_t inc = j0 < 8 ? (KVB >> 4) : -(KVB >> 4);
#pragma unroll 1
    for (; j0 <= jj; j0++)
#pragma unroll
      for (int u = 0; u < 2; u++) {
        mbar_wait_u(bar, 0); bar += 8;
        wg_fence();
        mma_qk_first(s, qa, dk0); mma_qk_acc(s, qa + 4, dk1);
        wg_commit();
        dk0 = addlo_r(dk0, inc); dk1 = addlo_r(dk1, inc);
        wg_wait<0>();
        fence_u<32>(s);
        if (u == 0 && (j0 & 1) == jodd) {
          fence_u<6>(oh);
#pragma unroll
          for (int i = 0; i < 6; i++) { const float2 v = __half22float2(*(__half2*)&oh[i]); o[2 * i] += v.x; o[2 * i + 1] += v.y; oh[i] = 0; }
          fence_u<6>(oh);
        }
        if (u == DONEU && (j0 == 3 || j0 == 13)) {
          if (elect_one()) mbar_arrive(sb + (j0 == 3 ? B_P2 : B_F1));
        }
#pragma unroll
        for (int hf = 0; hf < 2; hf++) {
#pragma unroll
          for (int i = hf * 8; i < hf * 8 + 8; i++) {
            if ((PMASK >> i) & 1) { p[2 * i] = exp_poly(s[2 * i], qa[4]); p[2 * i + 1] = exp_poly(s[2 * i + 1], qa[4]); }
            else { p[2 * i] = exp_mufu(s[2 * i]); p[2 * i + 1] = exp_mufu(s[2 * i + 1]); }
          }
          wg_fence();
#pragma unroll
          for (int i = hf * 4; i < hf * 4 + 4; i++) mma_pv(oh, p + 4 * i, dv[i]);
        }
        wg_commit();
#pragma unroll
        for (int i = 0; i < 8; i++) dv[i] = addlo_r(dv[i], inc);
      }
    wg_wait<0>();
    fence_u<6>(oh);
#pragma unroll
    for (int i = 0; i < 6; i++) { const float2 v = __half22float2(*(__half2*)&oh[i]); o[2 * i] += v.x; o[2 * i + 1] += v.y; }
    TQ(2 * jj);
    const int tid = fresh_tid(), bid = fresh_bid(), lane = tid & 31, g = lane >> 2, t = lane & 3;
    const int wg = __shfl_sync(~0u, tid >> 7, 0), wp = __shfl_sync(~0u, (tid >> 5) & 3, 0);
    const int h = bid >> 2, part = bid & 3, odd = h & 1, rloc = wg * 128 + wp * 16 + g;
    const float* gate = (const float*)(sm + SM_GATE) + rloc;
    const int src = (lane & ~3) | (odd ? 0 : 2);
    if (jj < 7) {
      mbar_wait(sb + B_AV, 0);
      uint32_t ph[2][10];
      const uint32_t phs = SM_AK + wg * 16384 + SLICE;
      feature_map2(ph, (sl + phs) >> 4, t, (sl + SM_WPHI) >> 4);
      bar_sync(4 + wg, 128);
#pragma unroll
      for (int tl = 0; tl < 2; tl++) {
        const uint32_t ad = sb + phs + (tl * 8 + wp * 2 + ((lane >> 3) & 1)) * 640 + (lane >> 4) * 128 + (lane & 7) * 16;
        stsm4(ad, ph[tl][0], ph[tl][1], ph[tl][2], ph[tl][3]);
        stsm4(ad + 256, ph[tl][4], ph[tl][5], ph[tl][6], ph[tl][7]);
        stsm2(ad + 512, ph[tl][8], ph[tl][9]);
      }
      fence_async();
      bar_sync(4 + wg, 128);
      float kv[12];
      wg_fence();
      mma_b24_tt0(kv, mkdesc((sl + phs) >> 4, 640, 128, 0), mkdesc((sl + phs - SLICE) >> 4, 384, 128, 0));
#pragma unroll
      for (int k = 1; k < 8; k++)
        mma_b24_tt(kv, mkdesc(((sl + phs) >> 4) + k * 80, 640, 128, 0), mkdesc(((sl + phs - SLICE) >> 4) + k * 48, 384, 128, 0));
      wg_commit();
      wg_wait<0>();
      fence_f<12>(kv);
      float* dst = g_kvs + h * 960 + (wp * 16 + g) * 24 + 2 * t;
      if (wp < 3) {
#pragma unroll
        for (int c = 0; c < 3; c++) asm volatile("red.relaxed.gpu.global.add.v2.f32 [%0], {%1,%2};" ::"l"(dst + 8 * c), "f"(kv[4 * c]), "f"(kv[4 * c + 1]) : "memory");
      }
      if (wp < 2) {
#pragma unroll
        for (int c = 0; c < 3; c++) asm volatile("red.relaxed.gpu.global.add.v2.f32 [%0], {%1,%2};" ::"l"(dst + 192 + 8 * c), "f"(kv[4 * c + 2]), "f"(kv[4 * c + 3]) : "memory");
      }
      __syncwarp();
      if (lane == 0) { mbar_arrive(sb + B_AK); if (wg == 0) mbar_arrive(sb + B_A0); }
    } else if ((jj & 7) == 7) {
      if (lane == 0 && wp == 0) TS(1, 16 + (jj >> 3) * 8 + wg);
      const float l0 = __shfl_sync(~0u, o[8], src), l1 = __shfl_sync(~0u, o[10], src);
      float chk = 0.f;
#pragma unroll
      for (int i = 0; i < 12; i++) chk += fabsf(o[i]);
      volatile uint32_t* flag = (volatile uint32_t*)(sm + SM_FLAG) + wg * 8 + (jj >> 3) * 4 + wp;
      const bool ok = *flag == 0 && l0 >= 64.f && l1 >= 64.f && chk < 1e30f;
      if (!__all_sync(~0u, ok)) { if (lane == 0) *flag = 1; }
      else store_o(o, __fdividef(1.f - gate[(jj >> 3) * 64], l0), __fdividef(1.f - gate[(jj >> 3) * 64 + 8], l1), 80, h, part * 512 + rloc + (jj >> 3) * 64, t);
#pragma unroll
      for (int i = 0; i < 12; i++) o[i] = 0.f;
      if (jj == 7) {
        mbar_wait(sb + B_Q1, 0);
        load_q(qa, sm, SM_Q1, 1);
        if (elect_one()) mbar_arrive(sb + B_QC);
      }
    } else {
      mbar_wait(sb + B_AQ, 0);
      uint32_t ph[2][10];
      const uint32_t kvi = (sl + SM_AQ + wg * SLICE) >> 4;
      feature_map2(ph, kvi, t, (sl + SM_WPHI) >> 4);
      mbar_wait(sb + B_KD, 0);
      bar_sync(4 + wg, 128);
      if ((tid & 127) < 120) {
        const int i = tid & 127, fc = i / 24;
        const float* kvs = (const float*)(sm + SM_KVS) + fc * 168 + i;
        *(uint4*)(sm + SM_AQ + wg * SLICE + i * 16) =
            make_uint4(pack_b(kvs[0], kvs[24]), pack_b(kvs[48], kvs[72]), pack_b(kvs[96], kvs[120]), pack_b(kvs[144], kvs[168]));
      }
      fence_async();
      bar_sync(4 + wg, 128);
#pragma unroll
      for (int tl = 0; tl < 2; tl++) {
        float d[12];
        uint32_t z[4] = {qa[4], qa[4], ph[tl][8], ph[tl][9]};
        fence_u<8>(ph[tl]); fence_u<4>(z);
        wg_fence();
        mma_b24_rs0(d, ph[tl], mkdesc(kvi, 384, 128, 0));
        mma_b24_rs(d, ph[tl] + 4, mkdesc(kvi + 48, 384, 128, 0));
        mma_b24_rs(d, z, mkdesc(kvi + 72, 384, 128, 0));
        wg_commit();
        wg_wait<0>();
        fence_f<12>(d);
        const float den0 = __shfl_sync(~0u, d[8], src) + 1e-6f, den1 = __shfl_sync(~0u, d[10], src) + 1e-6f;
        store_o(d, __fdividef(gate[tl * 64], den0), __fdividef(gate[tl * 64 + 8], den1), 0, h, part * 512 + rloc + tl * 64, t);
      }
      bar_sync(4 + wg, 128);
      if (wp == 3 && lane == 0) mbar_arrive(sb + B_QD);
    }
    __syncwarp();
    TQ(2 * jj + 1);
    fence_u<8>(qa);
  }
  bar_sync(8, 512);
  TQ(33);
  {
    const int tid = fresh_tid(), bid = fresh_bid(), lane = tid & 31;
    const int wg = __shfl_sync(~0u, tid >> 7, 0), wp = __shfl_sync(~0u, (tid >> 5) & 3, 0);
    if (__any_sync(~0u, ((const uint32_t*)(sm + SM_FLAG))[lane] != 0)) attn_fallback((const uint32_t*)(sm + SM_FLAG), bid >> 2, bid & 3, P.x, P.wB);
    if (wg == 3 && wp == 0) {
      bar_arrive(10, 64);
      if (lane == 0) { signal(C_OB + bid * 8); TS(2, 0); }
    }
    if (wg < 2) {
      float acc[40];
#pragma unroll 1
      for (int it = 0; it < 20; it++) {
        const int s = it & 7;
        bool rel = it > 0 && it <= 12;
        if (!mbar_test_wg(sb + B_OF + 8 * s, (it >> 3) & 1, 4 + wg)) {
          wg_wait<0>();
          if (rel && (tid & 127) < 2) mbar_arrive_cluster(sb + B_OE + 8 * ((it - 1) & 7), tid & 1);
          rel = false;
          mbar_wait(sb + B_OF + 8 * s, (it >> 3) & 1);
        }
        if (tid == 0 && (it == 0 || it == 10)) TS(2, 2 + (it == 10));
        const uint32_t aa = (sl + o_slot(s) + wg * 1024) >> 4, wa = (sl + o_slot(s) + O_AB) >> 4;
        wg_fence();
#pragma unroll
        for (int k = 0; k < 4; k++) mma_n80(acc, mkdesc(aa + 256 * k, 2048, 128, 0), mkdesc(wa + 160 * k, 1280, 128, 0), (it | k) != 0);
        wg_commit();
        wg_wait<1>();
        if (rel && (tid & 127) < 2) mbar_arrive_cluster(sb + B_OE + 8 * ((it - 1) & 7), tid & 1);
      }
      wg_wait<0>();
      fence_f<40>(acc);
      if (tid == 0) TS(2, 4);
      TQ(36);
      const uint32_t stg = sb + o_slot(6) + wg * 10240;
      const uint32_t ad = stg + (wp * 16 + ((lane >> 3) & 1) * 8 + (lane & 7)) * 160 + (lane >> 4) * 16;
      bar_sync(1, 256);
#pragma unroll
      for (int i = 0; i < 5; i++)
        stsm4(ad + i * 32, pack_b(acc[8 * i], acc[8 * i + 1]), pack_b(acc[8 * i + 2], acc[8 * i + 3]), pack_b(acc[8 * i + 4], acc[8 * i + 5]), pack_b(acc[8 * i + 6], acc[8 * i + 7]));
      fence_async();
      bar_sync(4 + wg, 128);
      if ((tid & 127) == 0) {
        tma2d_store(&P.tmOut, stg, (bid & 7) * 80, (bid >> 3) * 128 + wg * 64);
        bulk_commit();
        asm volatile("cp.async.bulk.wait_group.read 0;" ::: "memory");
        if (tid == 0) TS(2, 5);
      }
    }
  }
  TQ(37);
  __syncwarp();
  cluster_sync();
}

typedef CUresult (*EncodeFn)(CUtensorMap*, CUtensorMapDataType, cuuint32_t, void*, const cuuint64_t*, const cuuint64_t*, const cuuint32_t*,
                             const cuuint32_t*, CUtensorMapInterleave, CUtensorMapSwizzle, CUtensorMapL2promotion, CUtensorMapFloatOOBfill);

void encode(EncodeFn fn, CUtensorMap* m, const void* p, int rank, const cuuint64_t* dims, const cuuint64_t* strides, const cuuint32_t* box, CUtensorMapSwizzle swz) {
  const cuuint32_t es[3] = {1, 1, 1};
  CUresult r = fn(m, CU_TENSOR_MAP_DATA_TYPE_BFLOAT16, rank, const_cast<void*>(p), dims, strides, box, es, CU_TENSOR_MAP_INTERLEAVE_NONE, swz,
                  CU_TENSOR_MAP_L2_PROMOTION_L2_256B, CU_TENSOR_MAP_FLOAT_OOB_FILL_NONE);
  if (r != CUDA_SUCCESS) fprintf(stderr, "tensor map encode failed: %d\n", (int)r);
}

}

extern "C" void kernel_launch(void* const* d_in, const int* in_sizes, int n_in, void* d_out, int out_size) {
  (void)in_sizes; (void)n_in; (void)out_size;
  static EncodeFn fn = nullptr;
  if (!fn) {
    void* p = nullptr;
    cudaDriverEntryPointQueryResult qr;
    cudaGetDriverEntryPoint("cuTensorMapEncodeTiled", &p, cudaEnableDefault, &qr);
    fn = (EncodeFn)p;
    cudaFuncSetAttribute(fused_kernel, cudaFuncAttributeMaxDynamicSharedMemorySize, SM_TOTAL);
  }
  Params P;
  P.x = (const __nv_bfloat16*)d_in[0];
  P.w_phi = (const __nv_bfloat16*)d_in[2];
  P.wB = (const __nv_bfloat16*)d_in[5];
  P.gate_w = (const __nv_bfloat16*)d_in[7];
  P.woA = (const __nv_bfloat16*)d_in[3];
  P.woB = (const __nv_bfloat16*)d_in[6];
  {
    const cuuint64_t d[2] = {640, 2048}, st[1] = {1280};
    const cuuint32_t box[2] = {64, 128}, obox[2] = {80, 64};
    encode(fn, &P.tmX, d_in[0], 2, d, st, box, CU_TENSOR_MAP_SWIZZLE_128B);
    encode(fn, &P.tmOut, d_out, 2, d, st, obox, CU_TENSOR_MAP_SWIZZLE_NONE);
  }
  {
    const cuuint64_t d[2] = {1920, 640}, st[1] = {3840};
    const cuuint32_t box[2] = {64, 32};
    encode(fn, &P.tmWA, d_in[1], 2, d, st, box, CU_TENSOR_MAP_SWIZZLE_128B);
    encode(fn, &P.tmWB, d_in[5], 2, d, st, box, CU_TENSOR_MAP_SWIZZLE_128B);
  }
  fused_kernel<<<128, 640, SM_TOTAL, cudaStreamPerThread>>>(P);
}
```

```cpp
#include <cuda_runtime.h>
#include <cuda_bf16.h>
#include <cuda_fp16.h>
#include <cuda.h>
#include <stdint.h>
#include <stdio.h>

#define STOPS0 0x8480u
#define STOPS1 0x8880u
#define NLOC 1
#define PFX 0
#define NPRE 13
namespace {

constexpr int S_ = 2048, D_ = 640, H_ = 32;
constexpr int SLICE = 6144;
constexpr int KVB = 2 * SLICE;
#define PMASKV 0xADADu
constexpr uint32_t PMASK = PMASKV;
constexpr float QSCALE = 0.32259298f;

__device__ __align__(1024) uint8_t g_qB[H_ * 16 * SLICE];
__device__ __align__(1024) uint8_t g_kvB[H_ * 16 * KVB];
__device__ __align__(1024) uint8_t g_A[3 * H_ * 16 * SLICE];
__device__ __align__(1024) uint8_t g_o[16 * 160 * 2048];
__device__ __align__(1024) uint8_t g_wo[8 * 20 * 10240];
__device__ __align__(128) float g_stat[H_ * 32];
__device__ __align__(16) float g_gate[S_];
__device__ __align__(16) float g_kvs[H_ * 40 * 24];
__device__ __align__(16) __nv_bfloat16 g_fb[H_ * S_ * 40];
constexpr int C_B = 0, C_EXIT = 64, C_OA = 96, C_KV = 224, C_A = C_KV + 32 * 32, C_OB = C_A + 4, C_N = C_A + 128 * 8;
__device__ __align__(128) unsigned int g_cnt[C_N];

#define TS(k, i) do {} while (0)
#define TQ(i) do {} while (0)
__device__ __forceinline__ uint32_t smem_u32(const void* p) { return (uint32_t)__cvta_generic_to_shared(p); }
__device__ __forceinline__ uint64_t mkdesc(uint32_t a16, uint32_t lbo, uint32_t sbo, uint32_t swz) {
  uint32_t lo = a16 + ((lbo >> 4) << 16);
  uint32_t hi = (sbo >> 4) | (swz << 30);
  return ((uint64_t)hi << 32) | lo;
}
template <int INC> __device__ __forceinline__ uint64_t addlo(uint64_t d) {
  asm volatile("{.reg .b32 lo, hi; mov.b64 {lo,hi}, %0; add.u32 lo, lo, %1; mov.b64 %0, {lo,hi};}" : "+l"(d) : "n"(INC));
  return d;
}
__device__ __forceinline__ uint64_t addlo_r(uint64_t d, uint32_t inc) {
  asm volatile("{.reg .b32 lo, hi; mov.b64 {lo,hi}, %0; add.u32 lo, lo, %1; mov.b64 %0, {lo,hi};}" : "+l"(d) : "r"(inc));
  return d;
}
__device__ __forceinline__ void wg_fence() { asm volatile("wgmma.fence.sync.aligned;" ::: "memory"); }
__device__ __forceinline__ void wg_commit() { asm volatile("wgmma.commit_group.sync.aligned;" ::: "memory"); }
template <int N> __device__ __forceinline__ void wg_wait() { asm volatile("wgmma.wait_group.sync.aligned %0;" ::"n"(N) : "memory"); }
template <int N> __device__ __forceinline__ void fence_f(float* r) {
#pragma unroll
  for (int i = 0; i < N; i++) asm volatile("" : "+f"(r[i])::"memory");
}
template <int N> __device__ __forceinline__ void fence_u(uint32_t* r) {
#pragma unroll
  for (int i = 0; i < N; i++) asm volatile("" : "+r"(r[i])::"memory");
}
__device__ __forceinline__ void mbar_init(uint32_t bar, uint32_t cnt) { asm volatile("mbarrier.init.shared::cta.b64 [%0], %1;" ::"r"(bar), "r"(cnt) : "memory"); }
__device__ __forceinline__ void mbar_expect_tx(uint32_t bar, uint32_t bytes) { asm volatile("mbarrier.arrive.expect_tx.shared::cta.b64 _, [%0], %1;" ::"r"(bar), "r"(bytes) : "memory"); }
__device__ __forceinline__ void mbar_wait(uint32_t bar, uint32_t parity) {
  asm volatile(
      "{\n.reg .pred p;\n.reg .u32 n;\nmov.u32 n, 0;\n"
      "W: mbarrier.try_wait.parity.shared::cta.b64 p, [%0], %1;\n@p bra D;\n"
      "add.u32 n, n, 1;\nsetp.lt.u32 p, n, 0x1000000;\n@p bra W;\ntrap;\nD:\n}" ::"r"(bar), "r"(parity) : "memory");
}
__device__ __forceinline__ bool mbar_test_wg(uint32_t bar, uint32_t parity, int id) {
  uint32_t r;
  asm volatile("{.reg .pred p, q; mbarrier.test_wait.parity.shared::cta.b64 p, [%1], %2; bar.red.and.pred q, %3, 128, p; selp.u32 %0, 1, 0, q;}"
               : "=r"(r) : "r"(bar), "r"(parity), "r"(id) : "memory");
  return r != 0;
}
__device__ __forceinline__ void mbar_wait_z(uint32_t bar, uint32_t parity) {
  asm volatile(
      "{\n.reg .pred p;\n.reg .u32 n;\nmov.u32 n, 0;\n"
      "W: mbarrier.try_wait.parity.shared::cta.b64 p, [%0], %1, 20000;\n@p bra D;\n"
      "add.u32 n, n, 1;\nsetp.lt.u32 p, n, 0x100000;\n@p bra W;\ntrap;\nD:\n}" ::"r"(bar), "r"(parity) : "memory");
}
__device__ __forceinline__ void mbar_wait_u(uint32_t bar, uint32_t parity) {
  asm volatile("{\n.reg .pred p;\nW: mbarrier.try_wait.parity.shared::cta.b64 p, [%0], %1;\n@p bra D;\nbra W;\nD:\n}" ::"r"(bar), "r"(parity) : "memory");
}
__device__ __forceinline__ void mbar_arrive_cluster(uint32_t bar, uint32_t cta) {
  asm volatile("{.reg .b32 r; mapa.shared::cluster.u32 r, %0, %1; mbarrier.arrive.shared::cluster.b64 _, [r];}" ::"r"(bar), "r"(cta) : "memory");
}
__device__ __forceinline__ void bulk_g2s(uint32_t dst, const void* src, uint32_t bytes, uint32_t bar) {
  asm volatile("cp.async.bulk.shared::cluster.global.mbarrier::complete_tx::bytes [%0], [%1], %2, [%3];" ::"r"(dst), "l"(src), "r"(bytes), "r"(bar) : "memory");
}
__device__ __forceinline__ void bulk_g2s_mc(uint32_t dst, const void* src, uint32_t bytes, uint32_t bar, uint16_t mask) {
  asm volatile("cp.async.bulk.shared::cluster.global.mbarrier::complete_tx::bytes.multicast::cluster [%0], [%1], %2, [%3], %4;" ::"r"(dst), "l"(src), "r"(bytes), "r"(bar), "h"(mask) : "memory");
}
__device__ __forceinline__ void bulk_s2g(void* dst, uint32_t src, uint32_t bytes) {
  asm volatile("cp.async.bulk.global.shared::cta.bulk_group [%0], [%1], %2;" ::"l"(dst), "r"(src), "r"(bytes) : "memory");
}
__device__ __forceinline__ void tma2d(uint32_t dst, const CUtensorMap* m, int c0, int c1, uint32_t bar) {
  asm volatile("cp.async.bulk.tensor.2d.shared::cluster.global.mbarrier::complete_tx::bytes [%0], [%1, {%3, %4}], [%2];" ::"r"(dst), "l"(m), "r"(bar), "r"(c0), "r"(c1) : "memory");
}
__device__ __forceinline__ void tma2d_mc(uint32_t dst, const CUtensorMap* m, int c0, int c1, uint32_t bar, uint16_t mask) {
  asm volatile("cp.async.bulk.tensor.2d.shared::cluster.global.mbarrier::complete_tx::bytes.multicast::cluster [%0], [%1, {%3, %4}], [%2], %5;" ::"r"(dst), "l"(m), "r"(bar), "r"(c0), "r"(c1), "h"(mask) : "memory");
}
__device__ __forceinline__ void tma2d_store(const CUtensorMap* m, uint32_t src, int c0, int c1) {
  asm volatile("cp.async.bulk.tensor.2d.global.shared::cta.bulk_group [%0, {%2, %3}], [%1];" ::"l"(m), "r"(src), "r"(c0), "r"(c1) : "memory");
}
__device__ __forceinline__ void bulk_commit() { asm volatile("cp.async.bulk.commit_group;" ::: "memory"); }
__device__ __forceinline__ void bulk_wait_all() { asm volatile("cp.async.bulk.wait_group 0;" ::: "memory"); }
__device__ __forceinline__ void fence_async() { asm volatile("fence.proxy.async.shared::cta;" ::: "memory"); }
__device__ __forceinline__ void bar_sync(int id, int n) { asm volatile("bar.sync %0, %1;" ::"r"(id), "r"(n) : "memory"); }
__device__ __forceinline__ void bar_arrive(int id, int n) { asm volatile("bar.arrive %0, %1;" ::"r"(id), "r"(n) : "memory"); }
__device__ __forceinline__ void mbar_arrive(uint32_t bar) { asm volatile("mbarrier.arrive.shared::cta.b64 _, [%0];" ::"r"(bar) : "memory"); }
__device__ __forceinline__ void fence_gpu() { asm volatile("fence.acq_rel.gpu;" ::: "memory"); }
__device__ __forceinline__ void fence_async_g() { asm volatile("fence.proxy.async.global;" ::: "memory"); }
__device__ __forceinline__ void signal(int c) { fence_gpu(); asm volatile("red.relaxed.gpu.global.add.u32 [%0], 1;" ::"l"(g_cnt + c) : "memory"); }
__device__ __forceinline__ void await(int c, uint32_t target) {
  asm volatile(
      "{\n.reg .pred p;\n.reg .u32 n, v;\nmov.u32 n, 0;\n"
      "W: ld.acquire.gpu.global.u32 v, [%0];\nsetp.ge.u32 p, v, %1;\n@p bra D;\n"
      "nanosleep.u32 64;\nadd.u32 n, n, 1;\nsetp.lt.u32 p, n, 0x400000;\n@p bra W;\ntrap;\nD:\n}" ::"l"(g_cnt + c), "r"(target) : "memory");
}
__device__ __forceinline__ void await_all(int c, uint32_t target) {
  asm volatile(
      "{\n.reg .pred p;\n.reg .u32 n, v;\nmov.u32 n, 0;\n"
      "W: ld.acquire.gpu.global.u32 v, [%0];\nsetp.ge.u32 p, v, %1;\nvote.sync.all.pred p, p, 0xffffffff;\n@p bra.uni D;\n"
      "nanosleep.u32 64;\nadd.u32 n, n, 1;\nsetp.lt.u32 p, n, 0x400000;\n@p bra.uni W;\ntrap;\nD:\n}" ::"l"(g_cnt + c), "r"(target) : "memory");
}
__device__ __forceinline__ uint32_t await_mask(int c, uint32_t need) {
  uint32_t m;
  asm volatile(
      "{\n.reg .pred p;\n.reg .u32 n, v;\nmov.u32 n, 0;\n"
      "W: ld.acquire.gpu.global.u32 v, [%1];\nsetp.ne.u32 p, v, 0;\nvote.sync.ballot.b32 %0, p, 0xffffffff;\n"
      "and.b32 v, %0, %2;\nsetp.eq.u32 p, v, %2;\n@p bra.uni D;\n"
      "add.u32 n, n, 1;\nsetp.lt.u32 p, n, 0x400000;\n@p bra.uni W;\ntrap;\nD:\n}" : "=r"(m) : "l"(g_cnt + c), "r"(need) : "memory");
  return m;
}
__device__ __forceinline__ bool elect_one() {
  uint32_t p;
  asm volatile("{.reg .pred p; elect.sync _|p, 0xffffffff; selp.u32 %0, 1, 0, p;}" : "=r"(p));
  return p != 0;
}
__device__ __forceinline__ int fresh_tid() { int v; asm volatile("mov.u32 %0, %%tid.x;" : "=r"(v)); return v < 128 ? v + 512 : v - 128; }
__device__ __forceinline__ int fresh_bid() { int v; asm volatile("mov.u32 %0, %%ctaid.x;" : "=r"(v)); return v; }
__device__ __forceinline__ void stsm2(uint32_t addr, uint32_t a, uint32_t b) {
  asm volatile("stmatrix.sync.aligned.m8n8.x2.shared.b16 [%0], {%1,%2};" ::"r"(addr), "r"(a), "r"(b) : "memory");
}
__device__ __forceinline__ uint4 lds128(uint32_t a) { uint4 v; asm volatile("ld.shared.v4.u32 {%0,%1,%2,%3}, [%4];" : "=r"(v.x), "=r"(v.y), "=r"(v.z), "=r"(v.w) : "r"(a) : "memory"); return v; }
__device__ __forceinline__ void stsm4(uint32_t addr, uint32_t a, uint32_t b, uint32_t c, uint32_t d) {
  asm volatile("stmatrix.sync.aligned.m8n8.x4.shared.b16 [%0], {%1,%2,%3,%4};" ::"r"(addr), "r"(a), "r"(b), "r"(c), "r"(d) : "memory");
}
__device__ __forceinline__ uint32_t pack_h(float lo, float hi) { uint32_t r; asm("cvt.rn.f16x2.f32 %0, %1, %2;" : "=r"(r) : "f"(hi), "f"(lo)); return r; }
__device__ __forceinline__ uint32_t pack_b(float lo, float hi) { uint32_t r; asm("cvt.rn.bf16x2.f32 %0, %1, %2;" : "=r"(r) : "f"(hi), "f"(lo)); return r; }
__device__ __forceinline__ float ex2f(float x) { float r; asm("ex2.approx.ftz.f32 %0, %1;" : "=f"(r) : "f"(x)); return r; }
__device__ __forceinline__ float bf_lo(uint32_t u) { return __uint_as_float(u << 16); }
__device__ __forceinline__ float bf_hi(uint32_t u) { return __uint_as_float(u & 0xffff0000u); }

#define F4(o) "+f"(d[o + 0]), "+f"(d[o + 1]), "+f"(d[o + 2]), "+f"(d[o + 3])
#define F8(o) F4(o), F4(o + 4)
#define F40(o) F8(o), F8(o + 8), F8(o + 16), F8(o + 24), F8(o + 32)
#define RU8(o) "+r"(d[o + 0]), "+r"(d[o + 1]), "+r"(d[o + 2]), "+r"(d[o + 3]), "+r"(d[o + 4]), "+r"(d[o + 5]), "+r"(d[o + 6]), "+r"(d[o + 7])
#define WU8(o) "=r"(d[o + 0]), "=r"(d[o + 1]), "=r"(d[o + 2]), "=r"(d[o + 3]), "=r"(d[o + 4]), "=r"(d[o + 5]), "=r"(d[o + 6]), "=r"(d[o + 7])
#define A4 "r"(a[0]), "r"(a[1]), "r"(a[2]), "r"(a[3])

__device__ __forceinline__ void mma_n128(float* d, uint64_t a, uint64_t b, int acc) {
  asm volatile(
      "{.reg .pred p; setp.ne.b32 p, %66, 0;\n"
      "wgmma.mma_async.sync.aligned.m64n128k16.f32.bf16.bf16 {"
      "%0,%1,%2,%3,%4,%5,%6,%7,%8,%9,%10,%11,%12,%13,%14,%15,%16,%17,%18,%19,%20,%21,%22,%23,"
      "%24,%25,%26,%27,%28,%29,%30,%31,%32,%33,%34,%35,%36,%37,%38,%39,%40,%41,%42,%43,%44,%45,%46,%47,"
      "%48,%49,%50,%51,%52,%53,%54,%55,%56,%57,%58,%59,%60,%61,%62,%63"
      "}, %64, %65, p, 1, 1, 0, 1;}"
      : F40(0), F8(40), F8(48), F8(56)
      : "l"(a), "l"(b), "r"(acc));
}
__device__ __forceinline__ void mma_n112(float* d, uint64_t a, uint64_t b, int acc) {
  asm volatile(
      "{.reg .pred p; setp.ne.b32 p, %58, 0;\n"
      "wgmma.mma_async.sync.aligned.m64n112k16.f32.bf16.bf16 {"
      "%0,%1,%2,%3,%4,%5,%6,%7,%8,%9,%10,%11,%12,%13,%14,%15,%16,%17,%18,%19,%20,%21,%22,%23,"
      "%24,%25,%26,%27,%28,%29,%30,%31,%32,%33,%34,%35,%36,%37,%38,%39,%40,%41,%42,%43,%44,%45,%46,%47,"
      "%48,%49,%50,%51,%52,%53,%54,%55"
      "}, %56, %57, p, 1, 1, 0, 1;}"
      : F40(0), F8(40), F8(48)
      : "l"(a), "l"(b), "r"(acc));
}
__device__ __forceinline__ void mma_n80(float* d, uint64_t a, uint64_t b, int acc) {
  asm volatile(
      "{.reg .pred p; setp.ne.b32 p, %42, 0;\n"
      "wgmma.mma_async.sync.aligned.m64n80k16.f32.bf16.bf16 {"
      "%0,%1,%2,%3,%4,%5,%6,%7,%8,%9,%10,%11,%12,%13,%14,%15,%16,%17,%18,%19,%20,%21,%22,%23,%24,%25,%26,%27,%28,%29,"
      "%30,%31,%32,%33,%34,%35,%36,%37,%38,%39}, %40, %41, p, 1, 1, 0, 1;}"
      : F40(0)
      : "l"(a), "l"(b), "r"(acc));
}
__device__ __forceinline__ void mma_qk_first(uint32_t* d, uint64_t a, uint64_t b) {
  asm volatile(
      "wgmma.mma_async.sync.aligned.m64n128k16.f16.f16.f16 {%0,%1,%2,%3,%4,%5,%6,%7,%8,%9,%10,%11,%12,%13,%14,%15,%16,%17,%18,%19,%20,%21,%22,%23,%24,%25,%26,%27,%28,%29,%30,%31}, %32, %33, 0, 1, 1, 0, 0;"
      : WU8(0), WU8(8), WU8(16), WU8(24)
      : "l"(a), "l"(b));
}
__device__ __forceinline__ void mma_qk_acc(uint32_t* d, uint64_t a, uint64_t b) {
  asm volatile(
      "wgmma.mma_async.sync.aligned.m64n128k16.f16.f16.f16 {%0,%1,%2,%3,%4,%5,%6,%7,%8,%9,%10,%11,%12,%13,%14,%15,%16,%17,%18,%19,%20,%21,%22,%23,%24,%25,%26,%27,%28,%29,%30,%31}, %32, %33, 1, 1, 1, 0, 0;"
      : RU8(0), RU8(8), RU8(16), RU8(24)
      : "l"(a), "l"(b));
}
__device__ __forceinline__ void mma_pv(uint32_t* d, const uint32_t* a, uint64_t b) {
  asm volatile("wgmma.mma_async.sync.aligned.m64n24k16.f16.f16.f16 {%0,%1,%2,%3,%4,%5}, {%6,%7,%8,%9}, %10, 1, 1, 1, 1;"
               : "+r"(d[0]), "+r"(d[1]), "+r"(d[2]), "+r"(d[3]), "+r"(d[4]), "+r"(d[5])
               : A4, "l"(b));
}
#define W4(o) "=f"(d[o + 0]), "=f"(d[o + 1]), "=f"(d[o + 2]), "=f"(d[o + 3])
__device__ __forceinline__ void mma_b48_rs0(float* d, const uint32_t* a, uint64_t b) {
  asm volatile("wgmma.mma_async.sync.aligned.m64n48k16.f32.bf16.bf16 {%0,%1,%2,%3,%4,%5,%6,%7,%8,%9,%10,%11,%12,%13,%14,%15,%16,%17,%18,%19,%20,%21,%22,%23}, {%24,%25,%26,%27}, %28, 0, 1, 1, 0;"
               : W4(0), W4(4), W4(8), W4(12), W4(16), W4(20)
               : A4, "l"(b));
}
__device__ __forceinline__ void mma_b48_rs(float* d, const uint32_t* a, uint64_t b) {
  asm volatile("wgmma.mma_async.sync.aligned.m64n48k16.f32.bf16.bf16 {%0,%1,%2,%3,%4,%5,%6,%7,%8,%9,%10,%11,%12,%13,%14,%15,%16,%17,%18,%19,%20,%21,%22,%23}, {%24,%25,%26,%27}, %28, 1, 1, 1, 0;"
               : F8(0), F8(8), F8(16)
               : A4, "l"(b));
}
__device__ __forceinline__ void mma_b8_rs0(float* d, const uint32_t* a, uint64_t b) {
  asm volatile("wgmma.mma_async.sync.aligned.m64n8k16.f32.bf16.bf16 {%0,%1,%2,%3}, {%4,%5,%6,%7}, %8, 0, 1, 1, 0;" : W4(0) : A4, "l"(b));
}
__device__ __forceinline__ void mma_b8_rs(float* d, const uint32_t* a, uint64_t b) {
  asm volatile("wgmma.mma_async.sync.aligned.m64n8k16.f32.bf16.bf16 {%0,%1,%2,%3}, {%4,%5,%6,%7}, %8, 1, 1, 1, 0;" : F4(0) : A4, "l"(b));
}
__device__ __forceinline__ uint32_t mul_b2(uint32_t a, uint32_t b) { uint32_t r; asm("mul.rn.bf16x2 %0, %1, %2;" : "=r"(r) : "r"(a), "r"(b)); return r; }
__device__ __forceinline__ void mma_b24_ss0(float* d, uint64_t a, uint64_t b) {
  asm volatile("wgmma.mma_async.sync.aligned.m64n24k16.f32.bf16.bf16 {%0,%1,%2,%3,%4,%5,%6,%7,%8,%9,%10,%11}, %12, %13, 0, 1, 1, 0, 0;"
               : W4(0), W4(4), W4(8)
               : "l"(a), "l"(b));
}
__device__ __forceinline__ void mma_b24_ss(float* d, uint64_t a, uint64_t b) {
  asm volatile("wgmma.mma_async.sync.aligned.m64n24k16.f32.bf16.bf16 {%0,%1,%2,%3,%4,%5,%6,%7,%8,%9,%10,%11}, %12, %13, 1, 1, 1, 0, 0;"
               : F4(0), F4(4), F4(8)
               : "l"(a), "l"(b));
}
__device__ __forceinline__ void mma_b24_tt0(float* d, uint64_t a, uint64_t b) {
  asm volatile("wgmma.mma_async.sync.aligned.m64n24k16.f32.bf16.bf16 {%0,%1,%2,%3,%4,%5,%6,%7,%8,%9,%10,%11}, %12, %13, 0, 1, 1, 1, 1;"
               : W4(0), W4(4), W4(8)
               : "l"(a), "l"(b));
}
__device__ __forceinline__ void mma_b24_tt(float* d, uint64_t a, uint64_t b) {
  asm volatile("wgmma.mma_async.sync.aligned.m64n24k16.f32.bf16.bf16 {%0,%1,%2,%3,%4,%5,%6,%7,%8,%9,%10,%11}, %12, %13, 1, 1, 1, 1, 1;"
               : F4(0), F4(4), F4(8)
               : "l"(a), "l"(b));
}

constexpr int G_XB = 16384, G_WB = 16384, G_PB = G_XB + 2 * G_WB;
constexpr int SM_STG = 3 * G_PB;
constexpr int SM_Q = 0, KV0 = 4 * SLICE;
constexpr int SM_PHI = KV0 + 4 * KVB;
constexpr int SM_AQ = KV0 + 14 * KVB;
constexpr int SM_MISC = SM_STG + 12 * SLICE;
constexpr int B_FULL = SM_MISC, B_EMPTY = B_FULL + 48, B_KV = B_EMPTY + 48, B_BD = B_KV + 256, B_QR = B_BD + 8, B_AV = B_QR + 8,
              B_AQ = B_AV + 8, B_KD = B_AQ + 8, B_QD = B_KD + 8, B_P = B_QD + 8, B_OF = B_P + 40, B_OE = B_OF + 64;
constexpr int SM_FLAG = SM_MISC + 640;
constexpr int SM_WPHI = SM_MISC + 768;
constexpr int SM_RED = SM_WPHI + 1536;
constexpr int SM_GATE = SM_RED + 256;
constexpr int SM_IND = SM_GATE + 2048;
constexpr int SM_KVI = SM_IND + 640;
constexpr int SM_ZERO = SM_KVI + 3840;
constexpr int SM_TOTAL = SM_ZERO + 1024;
constexpr int O_AB = 16384, O_WB = 10240, O_STB = O_AB + O_WB;
__host__ __device__ constexpr int o_slot(int i) { return SM_MISC - (i + 1) * O_STB; }

template <bool BR_B>
__device__ __forceinline__ void g_epilogue(float* acc, uint32_t stg, int ct, int w, int wp, int lane) {
  const int t = lane & 3, hf = (lane >> 3) & 1, csel = lane >> 4, r = lane & 7;
  const int Rw = w * 64 + wp * 16;
  const uint32_t offK = Rw * 16 + hf * 128 + r * 16, offV = (Rw / 8 + hf) * 384 + r * 16;
  const bool p0 = (PMASK >> (Rw / 8)) & 1, p1 = (PMASK >> (Rw / 8 + 1)) & 1;
  const bool lo = t < 2, ev = !(t & 1);
#pragma unroll
  for (int j = 0; j < 6; j++) {
    const int type = (ct * 12 + 2 * j) >> 5;
    float* a = acc + 20 * j;
    uint32_t aug0, aug1, q[10];
    if (BR_B) {
      const float s0 = type == 0 ? QSCALE : (type == 1 && p0) ? 0.001953125f : 1.f;
      const float s1 = type == 0 ? QSCALE : (type == 1 && p1) ? 0.001953125f : 1.f;
      aug0 = (type == 0 || !ev) ? 0u : (type == 1 && p0) ? 0x18001800u : 0x00003C00u;
      aug1 = (type == 0 || !ev) ? 0u : (type == 1 && p1) ? 0x18001800u : 0x00003C00u;
#pragma unroll
      for (int i = 0; i < 5; i++) { q[2 * i] = pack_h(a[4 * i] * s0, a[4 * i + 1] * s0); q[2 * i + 1] = pack_h(a[4 * i + 2] * s1, a[4 * i + 3] * s1); }
    } else {
      aug0 = aug1 = (type == 2 && ev) ? 0x00003F80u : 0u;
#pragma unroll
      for (int i = 0; i < 10; i++) q[i] = pack_b(a[2 * i], a[2 * i + 1]);
    }
    const uint32_t base = stg + 2 * j * SLICE + (type == 2 ? offV : offK);
    const uint32_t cs = type == 2 ? 128 : 2048;
    stsm4(base + csel * cs, q[0], q[1], q[2], q[3]);
    stsm4(base + 2 * cs + csel * SLICE, lo ? q[4] : aug0, lo ? q[5] : aug1, lo ? aug0 : q[4], lo ? aug1 : q[5]);
    stsm4(base + SLICE + csel * cs, q[6], q[7], q[8], q[9]);
  }
}

__device__ __forceinline__ uint32_t exp_mufu(uint32_t s) { uint32_t r; asm("ex2.approx.f16x2 %0, %1;" : "=r"(r) : "r"(s)); return r; }
__device__ __forceinline__ uint32_t hfma(uint32_t a, uint32_t b, uint32_t c) { uint32_t r; asm("fma.rn.f16x2 %0, %1, %2, %3;" : "=r"(r) : "r"(a), "r"(b), "r"(c)); return r; }
__device__ __forceinline__ uint32_t hfma_relu(uint32_t a, uint32_t b, uint32_t c) { uint32_t r; asm("fma.rn.relu.f16x2 %0, %1, %2, %3;" : "=r"(r) : "r"(a), "r"(b), "r"(c)); return r; }
#define D2(x) ((x) * 0x10001u)
__device__ __forceinline__ uint32_t exp_poly(uint32_t u, uint32_t zero) {
  uint32_t r = hfma_relu(u, D2(0x0200u), 0u);
  uint32_t f = hfma(r, D2(0xF800u), u);
  uint32_t w = hfma(f, D2(0x60fcu), D2(0x457fu));
  w = hfma(f, w, D2(0x27d8u));
  w = hfma_relu(f, w, D2(0x05a8u));
  return __funnelshift_l(zero, r, 10) + w;
}

__device__ __forceinline__ void phi_logits(float* d, uint32_t img16, uint32_t wphi16) {
  mma_b24_ss0(d, mkdesc(img16, 2048, 128, 0), mkdesc(wphi16, 384, 128, 0));
  mma_b24_ss(d, mkdesc(img16 + 128, 2048, 128, 0), mkdesc(wphi16 + 48, 384, 128, 0));
}
__device__ __forceinline__ void phi_exp(uint32_t* e, float* d, int t, uint32_t zero) {
  fence_f<12>(d);
#pragma unroll
  for (int i = 0; i < 12; i++) d[i] *= 1.4426950408889634f;
  const bool lo = t < 2;
  const uint32_t sgn = lo ? 0u : 0x80000000u;
#pragma unroll
  for (int hf = 0; hf < 2; hf++) {
    const float* x = d + 2 * hf;
    e[hf] = pack_b(ex2f(x[0]), ex2f(x[1])); e[2 + hf] = pack_b(ex2f(x[4]), ex2f(x[5]));
    e[4 + hf] = pack_b(ex2f(__uint_as_float(__float_as_uint(x[8]) ^ sgn)), ex2f(__uint_as_float(__float_as_uint(x[9]) ^ sgn)));
    e[6 + hf] = pack_b(ex2f(-x[0]), ex2f(-x[1])); e[10 + hf] = pack_b(ex2f(-x[4]), ex2f(-x[5]));
  }
  float am[3];
#pragma unroll
  for (int i = 0; i < 3; i++) am[i] = fmaxf(fmaxf(fabsf(d[4 * i]), fabsf(d[4 * i + 1])), fmaxf(fabsf(d[4 * i + 2]), fabsf(d[4 * i + 3])));
  if (!__all_sync(~0u, fmaxf(fmaxf(am[0], am[1]), am[2]) <= 40.f)) {
#pragma unroll
    for (int hf = 0; hf < 2; hf++) {
      const float* x = d + 2 * hf;
      float mx = fmaxf(fmaxf(fmaxf(x[0], x[1]), fmaxf(x[4], x[5])), fmaxf(x[8], x[9]));
      float mn = fminf(fminf(fminf(x[0], x[1]), fminf(x[4], x[5])), fminf(x[8], x[9]));
      mx = fmaxf(mx, __shfl_xor_sync(~0u, mx, 1)); mn = fminf(mn, __shfl_xor_sync(~0u, mn, 1));
      mx = fmaxf(mx, __shfl_xor_sync(~0u, mx, 2)); mn = fminf(mn, __shfl_xor_sync(~0u, mn, 2));
      e[hf] = pack_b(ex2f(x[0] - mx), ex2f(x[1] - mx)); e[2 + hf] = pack_b(ex2f(x[4] - mx), ex2f(x[5] - mx));
      e[4 + hf] = pack_b(ex2f(lo ? x[8] - mx : mn - x[8]), ex2f(lo ? x[9] - mx : mn - x[9]));
      e[6 + hf] = pack_b(ex2f(mn - x[0]), ex2f(mn - x[1])); e[10 + hf] = pack_b(ex2f(mn - x[4]), ex2f(mn - x[5]));
    }
  }
  e[8] = zero; e[9] = zero;
  fence_u<12>(e);
}

__device__ __forceinline__ void phi_out(uint32_t* v, float* d, const float* gate, int src) {
  fence_f<24>(d);
#pragma unroll
  for (int hf = 0; hf < 2; hf++) {
    const float rp = __fdividef(1.f, d[9 + 2 * hf]), rn = __fdividef(1.f, d[21 + 2 * hf]);
    const float sc = __fdividef(gate[8 * hf], fmaf(d[8 + 2 * hf], rp, fmaf(d[20 + 2 * hf], rn, 1e-6f)));
    const float a = __shfl_sync(~0u, rp * sc, src), b = __shfl_sync(~0u, rn * sc, src);
#pragma unroll
    for (int c = 0; c < 3; c++)
      v[2 * c + hf] = pack_b(fmaf(d[12 + 4 * c + 2 * hf], b, d[4 * c + 2 * hf] * a), fmaf(d[13 + 4 * c + 2 * hf], b, d[4 * c + 2 * hf + 1] * a));
  }
}

__device__ __forceinline__ void store_o(const uint32_t* v, int cbase, int h, int row, int t) {
  uint32_t* p = (uint32_t*)(g_o + ((row >> 7) * 160 + cbase + (h >> 1) * 5) * 2048 + (row & 127) * 16) + t;
  uint32_t* p0 = p + ((h & 1) ? 1536 : 0);
  p0[0] = v[0]; p0[32] = v[1]; p0[512] = v[2]; p0[544] = v[3];
  if ((t >> 1) == (h & 1)) { p[1024] = v[4]; p[1056] = v[5]; }
}

__device__ __noinline__ void attn_fallback(const uint32_t* flags, int h, int part, const __nv_bfloat16* x, const __nv_bfloat16* wB) {
  __nv_bfloat16* kv = g_fb + (size_t)h * S_ * 40;
  const int tid = fresh_tid();
  for (int i = tid; i < S_ * 40; i += 512) {
    const int tok = i / 40, c = i % 40;
    const __nv_bfloat16* xr = x + (size_t)tok * D_;
    const __nv_bfloat16* wc = wB + (c < 20 ? 640 + h * 20 + c : 1280 + h * 20 + c - 20);
    float acc = 0.f;
    for (int k = 0; k < D_; k++) acc += __bfloat162float(xr[k]) * __bfloat162float(wc[(size_t)k * 1920]);
    kv[i] = __float2bfloat16(acc);
  }
  bar_sync(8, 512);
  const int warp = tid >> 5, lane = tid & 31;
  for (int wt = warp; wt < 32; wt += 16) {
    if (!flags[wt]) continue;
    for (int rr = 0; rr < 16; rr++) {
      const int row = part * 512 + wt * 16 + rr;
      float qv = 0.f;
      if (lane < 20) {
        for (int k = 0; k < D_; k++) qv += __bfloat162float(x[(size_t)row * D_ + k]) * __bfloat162float(wB[(size_t)k * 1920 + h * 20 + lane]);
        qv = __bfloat162float(__float2bfloat16(qv)) * QSCALE;
      }
      float m = -INFINITY, l = 0.f, o[20];
#pragma unroll
      for (int d = 0; d < 20; d++) o[d] = 0.f;
      for (int j = lane; j < S_; j += 32) {
        float s = 0.f;
#pragma unroll
        for (int d = 0; d < 20; d++) s += __shfl_sync(~0u, qv, d) * __bfloat162float(kv[j * 40 + d]);
        const float mn = fmaxf(m, s), c = exp2f(m - mn), p = exp2f(s - mn);
        l = l * c + p;
#pragma unroll
        for (int d = 0; d < 20; d++) o[d] = o[d] * c + p * __bfloat162float(kv[j * 40 + 20 + d]);
        m = mn;
      }
      float mg = m;
#pragma unroll
      for (int of = 16; of; of >>= 1) mg = fmaxf(mg, __shfl_xor_sync(~0u, mg, of));
      const float c = exp2f(m - mg);
      l *= c;
#pragma unroll
      for (int of = 16; of; of >>= 1) l += __shfl_xor_sync(~0u, l, of);
      const float sc = (1.f - __ldcg(g_gate + row)) / l;
#pragma unroll
      for (int d = 0; d < 20; d++) {
        float v = o[d] * c;
#pragma unroll
        for (int of = 16; of; of >>= 1) v += __shfl_xor_sync(~0u, v, of);
        const int col = h * 20 + d;
        if (lane == 0) *(__nv_bfloat16*)(g_o + ((size_t)(row >> 7) * 160 + 80 + (col >> 3)) * 2048 + (row & 127) * 16 + (col & 7) * 2) = __float2bfloat16(v * sc);
      }
    }
  }
  bar_sync(8, 512);
}

__device__ __forceinline__ void prep_q(uint8_t* sm, uint32_t sb, int i, int odd) {
  const uint32_t st = ((const uint32_t*)(sm + SM_RED))[i & 31];
  const float kn2 = __uint_as_float(__reduce_max_sync(~0u, (i & 16) ? 0u : st)), vmx = __uint_as_float(__reduce_max_sync(~0u, (i & 16) ? st : 0u));
  const bool head_ok = kn2 <= 1048576.f && vmx <= 32768.f && vmx >= 0.00390625f;
#pragma unroll
  for (int u = 0; u < 2; u++) {
    const int row = i + 256 * u;
    const uint32_t ad = sb + SM_Q + (row >> 7) * SLICE + (row & 127) * 16;
    const uint4 c0 = lds128(ad), c1 = lds128(ad + 2048), c2 = lds128(ad + 4096);
    const uint32_t v[12] = {c0.x, c0.y, c0.z, c0.w, c1.x, c1.y, c1.z, c1.w, c2.x, c2.y, c2.z, c2.w};
    float n0 = 0.f, n1 = 0.f;
#pragma unroll
    for (int c = 0; c < 12; c++) { const float2 a = __half22float2(*(const __half2*)&v[c]); n0 = fmaf(a.x, a.x, n0); n1 = fmaf(a.y, a.y, n1); }
    n0 += n1;
    float r;
    asm("sqrt.approx.f32 %0, %1;" : "=f"(r) : "f"(n0 * kn2));
    const float b = r * 1.01f + 0.05f;
    *(uint32_t*)(sm + SM_Q + (row >> 7) * SLICE + 4096 + (row & 127) * 16 + (odd ? 0 : 8)) = pack_h(-fmaxf(0.f, ceilf(b) - 15.f), 13.5f);
    if (!(head_ok && b <= 30.f && n0 <= 1048576.f)) ((volatile uint32_t*)(sm + SM_FLAG))[row >> 4] = 1;
  }
}

struct Params {
  CUtensorMap tmX, tmWB, tmWA, tmOut;
  const __nv_bfloat16 *x, *gate_w, *w_phi, *wB, *wA, *woA, *woB;
};

__device__ __forceinline__ void agent_g(const Params& P, uint32_t sb) {
  const int bid = blockIdx.x, rank = bid & 1, lane = threadIdx.x & 31;
  const int pr = bid >> 1, rt = (pr & 7) * 2 + rank, ct = pr >> 3, h = bid >> 2, part = bid & 3;
  asm volatile("barrier.cluster.wait.aligned;" ::: "memory");
  if (elect_one()) {
#pragma unroll
    for (int it = NLOC; it < 6; it++) {
      const int s = (it + 2) % 6;
      const uint32_t st = sb + (s >> 1) * G_PB + G_XB + (s & 1) * G_WB + rank * 8192, fb = sb + B_FULL + 8 * s;
      tma2d_mc(st, &P.tmWB, ct * 240 + rank * 128, it * 32, fb, 3);
      tma2d_mc(st + 4096, &P.tmWB, ct * 240 + rank * 128 + 64, it * 32, fb, 3);
    }
    asm volatile("prefetch.tensormap [%0];" ::"l"(&P.tmWA) : "memory");
  }
  {
    int s = 2, ph = 0;
#pragma unroll 1
    for (int it = 6; it < 40; it++) {
      const int kb = it >= 20 ? it - 20 : it;
      const uint32_t st = sb + (s >> 1) * G_PB + G_XB + (s & 1) * G_WB + rank * 8192, fb = sb + B_FULL + 8 * s;
      const CUtensorMap* wm = it >= 20 ? &P.tmWA : &P.tmWB;
      mbar_wait_z(sb + B_EMPTY + 8 * s, ph);
      if (elect_one()) {
        mbar_expect_tx(fb, (s & 1) ? G_WB : G_XB + G_WB);
        if (s & 1) tma2d(sb + (s >> 1) * G_PB, &P.tmX, (kb - 1) * 32, rt * 128, fb - 8);
        tma2d_mc(st, wm, ct * 240 + rank * 128, kb * 32, fb, 3);
        tma2d_mc(st + 4096, wm, ct * 240 + rank * 128 + 64, kb * 32, fb, 3);
      }
      if (s == 1) ph ^= 1;
      if (++s == 6) s = 0;
    }
  }
  const uint8_t* kvsrc = g_kvB + (size_t)h * 16 * KVB;
  await(C_B, 128);
  if (lane == 0) TS(0, 11);
  mbar_wait_z(sb + B_EMPTY + 8, 1);
  if (elect_one()) {
    fence_async_g();
    mbar_expect_tx(sb + B_BD, 4 * SLICE + 2048 + 128);
    bulk_g2s(sb + SM_Q, g_qB + ((size_t)h * 16 + part * 4) * SLICE, 4 * SLICE, sb + B_BD);
    bulk_g2s(sb + SM_RED, g_stat + h * 32, 128, sb + B_BD);
    bulk_g2s(sb + SM_GATE, g_gate + part * 512, 2048, sb + B_BD);
#pragma unroll
    for (int j = 0; j < 2; j++) { mbar_expect_tx(sb + B_KV + 8 * j, KVB); bulk_g2s(sb + KV0 + j * KVB, kvsrc + j * KVB, KVB, sb + B_KV + 8 * j); }
  }
#pragma unroll
  for (int q = 1; q < 3; q++) {
    mbar_wait_z(sb + B_EMPTY + 16 * q + 8, 0);
    if (elect_one()) {
#pragma unroll
      for (int j = 4 * q - 2; j < 4 * q + 2; j++) { mbar_expect_tx(sb + B_KV + 8 * j, KVB); bulk_g2s(sb + KV0 + j * KVB, kvsrc + j * KVB, KVB, sb + B_KV + 8 * j); }
    }
  }
  bar_sync(9, 288);
  if (lane == 0) {
#pragma unroll
    for (int q = 0; q < 12; q++) bulk_s2g(g_A + ((size_t)(ct * 12 + q) * 16 + rt) * SLICE, sb + SM_STG + q * SLICE, SLICE);
    bulk_commit();
    bulk_wait_all();
  }
  __syncwarp();
  if (elect_one()) {
#pragma unroll
    for (int j = 10; j < 16; j++) { mbar_expect_tx(sb + B_KV + 8 * j, KVB); bulk_g2s(sb + KV0 + j * KVB, kvsrc + j * KVB, KVB, sb + B_KV + 8 * j); }
  }
  if (lane == 0) { signal(C_A + bid * 8); TS(0, 14); }
  {
    const int l12 = lane % 12, c2 = ((l12 >> 2) * 32 + h) / 12, r2 = part * 4 + (l12 & 3);
    await_all(C_A + (((c2 * 8 + (r2 >> 1)) << 1) | (r2 & 1)) * 8, 1);
  }
  mbar_wait_z(sb + B_P, 0);
  if (elect_one()) {
    fence_async_g();
    mbar_expect_tx(sb + B_AV, 8 * SLICE);
#pragma unroll
    for (int q = 0; q < 4; q++) {
      bulk_g2s(sb + KV0 + q * KVB + SLICE, g_A + ((size_t)(H_ + h) * 16 + part * 4 + q) * SLICE, SLICE, sb + B_AV);
      bulk_g2s(sb + KV0 + q * KVB, g_A + ((size_t)(2 * H_ + h) * 16 + part * 4 + q) * SLICE, SLICE, sb + B_AV);
    }
  }
  mbar_wait_z(sb + B_P + 8, 0);
  if (lane == 0) TS(0, 16);
}

__device__ __forceinline__ void branch_a(uint8_t* sm, uint32_t sb) {
  const int tid = fresh_tid(), bid = fresh_bid(), lane = tid & 31, g = lane >> 2, t = lane & 3;
  const int wp = __shfl_sync(~0u, (tid >> 5) & 3, 0), h = bid >> 2, part = bid & 3;
  const uint32_t sl = sb & 0x3FFFF, wphi16 = (sl + SM_WPHI) >> 4;
  const uint32_t zero = *(volatile uint32_t*)(sm + SM_ZERO);
  {
    const uint32_t ad = sb + SM_PHI + (wp * 2 + ((lane >> 3) & 1)) * 640 + (lane >> 4) * 128 + (lane & 7) * 16;
    const uint32_t ind16 = (sl + SM_IND) >> 4;
    float* dst = g_kvs + h * 960 + (wp * 16 + g) * 24 + 2 * t;
    mbar_wait_z(sb + B_AV, 0);
    float d[12];
    wg_fence();
    phi_logits(d, (sl + KV0 + SLICE) >> 4, wphi16);
    wg_commit();
    wg_wait<0>();
#pragma unroll 1
    for (int i = 0; i < 8; i++) {
      const uint32_t unit = sl + KV0 + (i >> 1) * KVB, buf = (i & 3) * 5120;
      {
        uint32_t e[12];
        phi_exp(e, d, t, zero);
        float z[4];
        const int nx = min(i + 1, 7);
        wg_fence();
        mma_b8_rs0(z, e, mkdesc(ind16, 128, 128, 0));
        mma_b8_rs(z, e + 4, mkdesc(ind16 + 16, 128, 128, 0));
        mma_b8_rs(z, e + 8, mkdesc(ind16 + 24, 128, 128, 0));
        phi_logits(d, (sl + KV0 + (nx >> 1) * KVB + SLICE + (nx & 1) * 1024) >> 4, wphi16);
        wg_commit();
        wg_wait<0>();
        fence_f<4>(z); fence_u<12>(e);
        uint32_t r[2];
#pragma unroll
        for (int hf = 0; hf < 2; hf++) r[hf] = __shfl_sync(~0u, pack_b(__fdividef(1.f, z[2 * hf]), __fdividef(1.f, z[2 * hf + 1])), lane & ~3);
        const uint32_t p0 = __byte_perm(r[0], 0, 0x1010), p1 = __byte_perm(r[1], 0, 0x1010), n0 = __byte_perm(r[0], 0, 0x3232), n1 = __byte_perm(r[1], 0, 0x3232);
        stsm4(ad + buf, mul_b2(e[0], p0), mul_b2(e[1], p1), mul_b2(e[2], p0), mul_b2(e[3], p1));
        stsm4(ad + buf + 256, mul_b2(e[4], t < 2 ? p0 : n0), mul_b2(e[5], t < 2 ? p1 : n1), mul_b2(e[6], n0), mul_b2(e[7], n1));
        stsm2(ad + buf + 512, mul_b2(e[10], n0), mul_b2(e[11], n1));
      }
      if ((i & 3) == 3) {
        fence_async();
        bar_sync(11, 128);
        float kv[12];
        wg_fence();
        mma_b24_tt0(kv, mkdesc((sl + SM_PHI) >> 4, 640, 128, 0), mkdesc((unit - KVB) >> 4, 384, 128, 0));
#pragma unroll
        for (int k = 1; k < 16; k++)
          mma_b24_tt(kv, mkdesc(((sl + SM_PHI) >> 4) + k * 80, 640, 128, 0), mkdesc(((unit - KVB + (k >> 3) * KVB) >> 4) + (k & 7) * 48, 384, 128, 0));
        wg_commit();
        wg_wait<0>();
        fence_f<12>(kv);
        if (wp < 3) {
#pragma unroll
          for (int c = 0; c < 3; c++) asm volatile("red.relaxed.gpu.global.add.v2.f32 [%0], {%1,%2};" ::"l"(dst + 8 * c), "f"(kv[4 * c]), "f"(kv[4 * c + 1]) : "memory");
        }
        if (wp < 2) {
#pragma unroll
          for (int c = 0; c < 3; c++) asm volatile("red.relaxed.gpu.global.add.v2.f32 [%0], {%1,%2};" ::"l"(dst + 192 + 8 * c), "f"(kv[4 * c + 2]), "f"(kv[4 * c + 3]) : "memory");
        }
        if (i == 3) bar_sync(11, 128);
      }
    }
    bar_sync(11, 128);
    if (tid == 608) { signal(C_KV + h * 32); TS(0, 17); }
    if (wp == 0) {
      if (elect_one()) {
        const uint8_t* kvsrc = g_kvB + (size_t)h * 16 * KVB;
#pragma unroll
        for (int j = 5; j >= 0; j--) { mbar_expect_tx(sb + B_KV + 248 - 8 * j, KVB); bulk_g2s(sb + KV0 + j * KVB, kvsrc + j * KVB, KVB, sb + B_KV + 248 - 8 * j); }
      }
      mbar_wait_z(sb + B_P + 32, 0);
      if (elect_one()) {
        mbar_expect_tx(sb + B_AQ, 4 * SLICE);
        bulk_g2s(sb + SM_AQ, g_A + ((size_t)h * 16 + part * 4) * SLICE, 4 * SLICE, sb + B_AQ);
      }
      await(C_KV + h * 32, 4);
    }
    bar_sync(11, 128);
  }
  if (tid == 512) TS(0, 18);
  const int zc = (h & 1) ? 16 : 20;
#pragma unroll
  for (int u = 0; u < 2; u++) {
    const int j = (tid & 127) + 128 * u, fc = j / 48, n = j % 48, dd = n % 24;
    if (j < 240) {
      const float* kvs = g_kvs + h * 960 + fc * 192 + dd;
      uint32_t w[4];
#pragma unroll
      for (int c = 0; c < 4; c++) w[c] = dd == zc + 1 ? 0x3F803F80u : pack_b(__ldcg(kvs + 48 * c), __ldcg(kvs + 48 * c + 24));
      const bool neg = n >= 24, k0 = (fc > 2) == neg, k1 = (fc > 1) == neg;
      *(uint4*)(sm + SM_KVI + j * 16) = make_uint4(k0 ? w[0] : 0u, k0 ? w[1] : 0u, k1 ? w[2] : 0u, k1 ? w[3] : 0u);
    }
  }
  fence_async();
  __syncwarp();
  if (lane == 0) mbar_arrive(sb + B_KD);
}

__device__ __forceinline__ void agent_t(uint32_t sb) {
  const int bid = fresh_bid(), rank = bid & 1, lane = fresh_tid() & 31, part = bid & 3;
  mbar_wait_z(sb + B_QD, 0);
  if (lane == 0) TS(0, 19);
  if (lane == 0) signal(C_OA + part * 32);
  const uint8_t* osrc = g_o + (size_t)(bid >> 3) * 160 * 2048;
  const uint8_t* wsrc = g_wo + (bid & 7) * 204800;
  await(C_OA + (bid >> 5) * 32, 32);
  if (lane == 0) TS(0, 20);
  mbar_wait_z(sb + B_P + 16, 0);
  if (lane == 0) TS(0, 21);
  if (elect_one()) {
    fence_async_g();
#pragma unroll
    for (int it = 0; it < 4; it++) {
      mbar_expect_tx(sb + B_OF + 8 * it, O_STB);
      bulk_g2s(sb + o_slot(it) + O_AB, wsrc + it * O_WB, O_WB, sb + B_OF + 8 * it);
      bulk_g2s(sb + o_slot(it), osrc + it * O_AB, O_AB, sb + B_OF + 8 * it);
    }
  }
  mbar_wait_z(sb + B_P + 24, 0);
  if (elect_one()) {
#pragma unroll
    for (int it = 4; it < 6; it++) {
      mbar_expect_tx(sb + B_OF + 8 * it, O_STB);
      bulk_g2s(sb + o_slot(it) + O_AB, wsrc + it * O_WB, O_WB, sb + B_OF + 8 * it);
      bulk_g2s(sb + o_slot(it), osrc + it * O_AB, O_AB, sb + B_OF + 8 * it);
    }
  }
#pragma unroll
  for (int it = 6; it < NPRE; it++) {
    const uint32_t st = sb + o_slot(it & 7), fb = sb + B_OF + 8 * (it & 7);
    mbar_wait_z(sb + B_OE + 8 * (it & 7), it >= 14);
    if (elect_one()) {
      mbar_expect_tx(fb, O_STB);
      if (it < 10) bulk_g2s_mc(st + rank * 8192, osrc + it * O_AB + rank * 8192, 8192, fb, 3);
      bulk_g2s(st + O_AB, wsrc + it * O_WB, O_WB, fb);
    }
  }
  const int ob = C_OB + (bid >> 5) * 8 + lane * 32;
  uint32_t ready = 0;
#pragma unroll
  for (int it = 10; it < 20; it++) {
    const uint32_t st = sb + o_slot(it & 7), fb = sb + B_OF + 8 * (it & 7);
    const int h0 = (it - 10) * 64 / 20, h1 = ((it - 10) * 64 + 63) / 20;
    const uint32_t need = (uint32_t)((2ull << h1) - (1ull << h0));
    if (it >= NPRE) {
      mbar_wait(sb + B_OE + 8 * (it & 7), it >= 14);
      if (elect_one()) { mbar_expect_tx(fb, O_STB); bulk_g2s(st + O_AB, wsrc + it * O_WB, O_WB, fb); }
    }
    if ((ready & need) != need) { ready = await_mask(ob, need); fence_async_g(); }
    if (elect_one()) {
      if (it == 10) TS(2, 1);
      bulk_g2s_mc(st + rank * 8192, osrc + it * O_AB + rank * 8192, 8192, fb, 3);
    }
  }
  uint32_t v = 0;
  if (lane == 0) v = atomicAdd(&g_cnt[C_EXIT], 1u);
  if (__shfl_sync(~0u, v, 0) == 127u) {
    g_cnt[C_KV + 32 * lane] = 0;
    if (lane < 7) g_cnt[32 * lane] = 0;
#pragma unroll
    for (int i = 0; i < 4; i++) { g_cnt[C_A + 8 * (lane + 32 * i)] = 0; g_cnt[C_OB + 8 * (lane + 32 * i)] = 0; }
  }
}

__global__ void __cluster_dims__(2, 1, 1) __launch_bounds__(640, 1) fused_kernel(const __grid_constant__ Params P) {
  extern __shared__ __align__(1024) uint8_t sm[];
  const uint32_t sb = __shfl_sync(~0u, smem_u32(sm), 0), sl = sb & 0x3FFFF;
  const int tid = fresh_tid(), wg = __shfl_sync(~0u, tid >> 7, 0), wp = __shfl_sync(~0u, (tid >> 5) & 3, 0), lane = tid & 31;
  const int bid = blockIdx.x;
  if (wg == 4 && wp == 0) {
    if (elect_one()) {
      TS(0, 0);
      const int rt = ((bid >> 1) & 7) * 2 + (bid & 1), ct = bid >> 4;
#pragma unroll
      for (int i = 0; i < 6; i++) mbar_init(sb + B_FULL + 8 * i, 1);
#pragma unroll
      for (int it = 0; it < 6; it++) {
        const int s = (it + 2) % 6;
        const uint32_t st = sb + (s >> 1) * G_PB, fb = sb + B_FULL + 8 * s;
        mbar_expect_tx(fb, (it & 1) ? G_WB : G_XB + G_WB);
        if (!(it & 1)) tma2d(st, &P.tmX, it * 32, rt * 128, fb);
        if (it < NLOC) {
#pragma unroll
          for (int q = 0; q < 4; q++) tma2d(st + G_XB + (s & 1) * G_WB + q * 4096, &P.tmWB, ct * 240 + q * 64, it * 32, fb);
        }
      }
#pragma unroll
      for (int i = 0; i < 6; i++) mbar_init(sb + B_EMPTY + 8 * i, 4);
      mbar_init(sb + B_BD, 1); mbar_init(sb + B_QR, 8);
    }
  }
  TQ(32);
  __syncthreads();
  asm volatile("barrier.cluster.arrive.release.aligned;" ::: "memory");
  if (wg == 4) {
    asm volatile("setmaxnreg.dec.sync.aligned.u32 32;");
    if (wp == 0) agent_g(P, sb);
    else asm volatile("barrier.cluster.wait.aligned;" ::: "memory");
    bar_sync(11, 128);
    asm volatile("setmaxnreg.inc.sync.aligned.u32 64;");
    branch_a(sm, sb);
    if (wp == 0) agent_t(sb);
    return;
  }
  asm volatile("barrier.cluster.wait.aligned;" ::: "memory");
  {
    const int pr = bid >> 1, rt = (pr & 7) * 2 + (bid & 1), ct = pr >> 3;
    const int h = bid >> 2, part = bid & 3, odd = h & 1;
    const uint32_t stg = sb + SM_STG;
    if (wg < 2) {
      asm volatile("setmaxnreg.inc.sync.aligned.u32 168;");
      float acc[120];
      int s = 2, ph = 0;
#pragma unroll 1
      for (int round = 0; round < 2; round++) {
        int prev = 0;
#pragma unroll 1
        for (int kb = 0; kb < 20; kb++) {
          mbar_wait(sb + B_FULL + 8 * s, ph);
          if (tid == 0 && kb == 0) TS(0, 1 + round * 5);
          const uint32_t xa = (sl + (s >> 1) * G_PB + wg * 8192 + (s & 1) * 64) >> 4, wa = (sl + (s >> 1) * G_PB + G_XB + (s & 1) * G_WB) >> 4;
          wg_fence();
#pragma unroll
          for (int k = 0; k < 2; k++) {
            mma_n128(acc, mkdesc(xa + 2 * k, 16, 1024, 1), mkdesc(wa + 128 * k, 4096, 1024, 1), (kb | k) != 0);
            mma_n112(acc + 64, mkdesc(xa + 2 * k, 16, 1024, 1), mkdesc(wa + 512 + 128 * k, 4096, 1024, 1), (kb | k) != 0);
          }
          wg_commit();
          if (kb > 0) {
            wg_wait<1>();
            if ((tid & 127) < 2) mbar_arrive_cluster(sb + B_EMPTY + 8 * prev, tid & 1);
          }
          prev = s;
          if (s == 1) ph ^= 1;
          if (++s == 6) s = 0;
        }
        wg_wait<0>();
        fence_f<120>(acc);
        if (tid == 0) TS(0, 3 + round * 5);
        if ((tid & 127) < 2) mbar_arrive_cluster(sb + B_EMPTY + 8 * prev, tid & 1);
        if (round == 0) {
          g_epilogue<true>(acc, stg, ct, wg, wp, lane);
          fence_async();
          bar_arrive(1, 416);
        } else {
          bar_sync(2, 416);
          g_epilogue<false>(acc, stg, ct, wg, wp, lane);
          fence_async();
          bar_arrive(9, 288);
        }
        if (tid == 0) TS(0, 4 + round * 5);
      }
      asm volatile("setmaxnreg.dec.sync.aligned.u32 104;");
    } else {
      asm volatile("setmaxnreg.dec.sync.aligned.u32 56;");
      const int i8 = tid - 256;
      {
        uint4 v[4];
        uint32_t off[4];
#pragma unroll
        for (int u = 0; u < 4; u++) {
          const uint32_t c = bid * 100 + min((i8 >> 3) + 32 * u, 99), grp = c / 80, pc = c - grp * 80, k = grp * 8 + (i8 & 7), cb = pc / 10;
          v[u] = __ldg((const uint4*)(k < 640 ? P.woA + k * 640 : P.woB + (k - 640) * 640) + pc);
          off[u] = cb * (204800 - 1280) + pc * 128 + grp * 1280 + (i8 & 7) * 16;
        }
        if (wg == 2 && wp < 3) {
          const int kc = i8 / 24, f = i8 - kc * 24, d0 = kc == 3 ? (odd ? -4 : 16) : kc * 8 + odd * 4;
          const uint16_t* wsrc = (const uint16_t*)P.w_phi + h * 400 + d0 * 20 + (f < 20 ? f : f - 4);
          const bool lo = kc < 2 || (kc == 3 && !odd), hi = kc < 2 || (kc == 3 && odd);
          uint32_t w[8];
#pragma unroll
          for (int e = 0; e < 8; e++) w[e] = (e < 4 ? lo : hi) ? __ldg(wsrc + e * 20) : 0u;
          *(uint4*)(sm + SM_WPHI + i8 * 16) = make_uint4(w[0] | w[1] << 16, w[2] | w[3] << 16, w[4] | w[5] << 16, w[6] | w[7] << 16);
        } else if (wg == 2) {
          ((uint32_t*)(sm + SM_FLAG))[i8 - 96] = 0;
          if (elect_one()) {
#pragma unroll
            for (int i = 0; i < 32; i++) mbar_init(sb + B_KV + 8 * i, 1);
#pragma unroll
            for (int i = 16; i < 26; i++) mbar_arrive(sb + B_KV + 8 * i);
            mbar_init(sb + B_AV, 1); mbar_init(sb + B_AQ, 1); mbar_init(sb + B_KD, 4); mbar_init(sb + B_QD, 16);
#pragma unroll
            for (int i = 0; i < 5; i++) mbar_init(sb + B_P + 8 * i, 16);
#pragma unroll
            for (int i = 0; i < 8; i++) { mbar_init(sb + B_OF + 8 * i, 1); mbar_init(sb + B_OE + 8 * i, 4); }
            asm volatile("fence.mbarrier_init.release.cluster;" ::: "memory");
          }
        } else {
          const int t7 = i8 - 128;
          ((uint2*)(sm + SM_ZERO))[t7] = make_uint2(0u, 0u);
          if (t7 < 80) {
            const int fc = t7 >> 4, n = (t7 >> 1) & 7, neg = (t7 & 1) ? fc > 1 : fc > 2;
            const uint32_t w = n == neg ? 0x3F803F80u : 0u;
            ((uint2*)(sm + SM_IND))[t7] = make_uint2(w, w);
          }
        }
        if (part == 0 && i8 < 240) ((float4*)g_kvs)[h * 240 + i8] = make_float4(0.f, 0.f, 0.f, 0.f);
        fence_async();
#pragma unroll
        for (int u = 0; u < 4; u++) *(uint4*)(g_wo + off[u]) = v[u];
      }
      {
        const int row = bid * 16 + (i8 >> 5) * 2;
        float z0 = 0.f, z1 = 0.f;
#pragma unroll
        for (int i = 0; i < 3; i++) {
          if (lane + 32 * i < 80) {
            const uint4 gw = __ldg((const uint4*)P.gate_w + lane + 32 * i);
            const uint4 a = __ldg((const uint4*)(P.x + row * D_) + lane + 32 * i), b = __ldg((const uint4*)(P.x + (row + 1) * D_) + lane + 32 * i);
            const uint32_t gv[4] = {gw.x, gw.y, gw.z, gw.w}, av[4] = {a.x, a.y, a.z, a.w}, bv[4] = {b.x, b.y, b.z, b.w};
#pragma unroll
            for (int e = 0; e < 4; e++) {
              const float gl = bf_lo(gv[e]), gh = bf_hi(gv[e]);
              z0 = fmaf(bf_lo(av[e]), gl, fmaf(bf_hi(av[e]), gh, z0));
              z1 = fmaf(bf_lo(bv[e]), gl, fmaf(bf_hi(bv[e]), gh, z1));
            }
          }
        }
        float z = (lane & 1) ? z1 : z0;
        z += __shfl_xor_sync(~0u, (lane & 1) ? z0 : z1, 1);
#pragma unroll
        for (int o = 16; o > 1; o >>= 1) z += __shfl_xor_sync(~0u, z, o);
        if (lane < 2) g_gate[row + lane] = __fdividef(1.f, 1.f + __expf(-z));
      }
      if (wg == 3) {
        const int t7 = tid & 127;
        bar_sync(1, 416);
        const bool pl = (PMASK >> (t7 >> 3)) & 1;
#pragma unroll 2
        for (int q = 0; q < 12; q++) {
          const int sidx = ct * 12 + q, type = sidx >> 5;
          if (type == 0) continue;
          const uint32_t ad = stg + q * SLICE + (type == 1 ? t7 * 16 : (t7 >> 3) * 384 + (t7 & 7) * 16), cs = type == 1 ? 2048 : 128;
          const uint4 c0 = lds128(ad), c1 = lds128(ad + cs), c2 = lds128(ad + 2 * cs);
          const uint32_t v[10] = {c0.x, c0.y, c0.z, c0.w, c1.x, c1.y, c1.z, c1.w, (q & 1) ? c2.z : c2.x, (q & 1) ? c2.w : c2.y};
          float r;
          if (type == 1) {
            float r1 = 0.f;
            r = 0.f;
#pragma unroll
            for (int i = 0; i < 10; i++) { const float2 f = __half22float2(*(const __half2*)&v[i]); r = fmaf(f.x, f.x, r); r1 = fmaf(f.y, f.y, r1); }
            r += r1;
            if (pl) r *= 262144.f;
          } else {
            uint32_t m = 0;
#pragma unroll
            for (int i = 0; i < 10; i++) m = __vmaxu2(m, v[i] & 0x7fff7fffu);
            m = max(m & 0xffffu, m >> 16);
            r = __half2float(__ushort_as_half((unsigned short)m));
          }
          const uint32_t u = __reduce_max_sync(~0u, __float_as_uint(r));
          if (lane == 0) ((uint32_t*)(sm + SM_RED))[q * 4 + wp] = u;
        }
        bar_arrive(2, 416);
        bar_sync(7, 128);
        if (t7 < 12) {
          const int sidx = ct * 12 + t7, type = sidx >> 5, head = sidx & 31;
          const uint4 u = *(const uint4*)(sm + SM_RED + t7 * 16);
          if (type != 0) g_stat[head * 32 + (type - 1) * 16 + rt] = __uint_as_float(max(max(u.x, u.y), max(u.z, u.w)));
        }
        fence_async();
        bar_arrive(3, 256);
      } else if (wp == 1) {
        bar_sync(1, 416);
        if (lane == 0) {
#pragma unroll 1
          for (int q = 0; q < 12; q++) {
            const int sidx = ct * 12 + q, type = sidx >> 5, head = sidx & 31;
            bulk_s2g(type == 0 ? g_qB + ((size_t)head * 16 + rt) * SLICE : g_kvB + ((size_t)head * 16 + rt) * KVB + (type - 1) * SLICE, stg + q * SLICE, SLICE);
            bulk_commit();
            asm volatile("cp.async.bulk.wait_group 1;" ::: "memory");
          }
          bulk_wait_all();
        }
        __syncwarp();
        bar_arrive(2, 416);
        bar_sync(3, 256);
        if (lane == 0) { signal(C_B); TS(0, 10); }
        __syncwarp();
      } else {
        bar_arrive(3, 256);
      }
      mbar_wait(sb + B_BD, 0);
      prep_q(sm, sb, tid - 256, odd);
      fence_async();
      __syncwarp();
      if (lane == 0) mbar_arrive(sb + B_QR);
      asm volatile("setmaxnreg.inc.sync.aligned.u32 104;");
    }
  }
  if (lane == 0 && wp == 0) TS(1, wg);
  TQ(35);
  uint32_t oh[6], s[32], p[32];
  float o[12];
  mbar_wait(sb + B_QR, 0);
  const uint32_t zero = *(volatile uint32_t*)(sm + SM_ZERO);
#pragma unroll
  for (int i = 0; i < 12; i++) o[i] = 0.f;
  if (lane == 0 && wp == 0) TS(1, 4 + wg);
  TQ(34);
  const uint32_t stops = wg < 2 ? STOPS0 : STOPS1;
#pragma unroll 1
  for (int j0 = 0; j0 < 16;) {
    const int jj = j0 + __ffs(stops >> j0) - 1;
    uint32_t bar = sb + B_KV + 16 * j0;
    const uint32_t k16 = (sl + KV0 + (j0 < 8 ? 2 * j0 : 31 - 2 * j0) * KVB) >> 4;
    const uint32_t qoff = SM_Q + wg * SLICE + (j0 >> 3) * 1024;
    const uint64_t dq0 = mkdesc((sl + qoff) >> 4, 2048, 128, 0), dq1 = mkdesc((sl + qoff + 4096) >> 4, SM_ZERO - 4096 - qoff, 128, 0);
    uint64_t dk0 = mkdesc(k16, 2048, 128, 0), dk1 = mkdesc(k16 + 256, 2048, 128, 0), dv[8];
#pragma unroll
    for (int i = 0; i < 8; i++) dv[i] = mkdesc(k16 + ((SLICE + i * 768) >> 4), 384, 128, 0);
#pragma unroll
    for (int i = 0; i < 6; i++) oh[i] = 0;
    fence_u<6>(oh);
    const uint32_t marks = j0 < 8 ? 0x2100u : 0x40300050u;
    const uint32_t inc = j0 < 8 ? (KVB >> 4) : -(KVB >> 4);
#pragma unroll 1
    for (; j0 <= jj; j0++)
#pragma unroll
      for (int u = 0; u < 2; u++) {
        mbar_wait_u(bar, 0); bar += 8;
        wg_fence();
        mma_qk_first(s, dq0, dk0); mma_qk_acc(s, dq1, dk1);
        wg_commit();
        dk0 = addlo_r(dk0, inc); dk1 = addlo_r(dk1, inc);
        wg_wait<0>();
        fence_u<32>(s);
        if (u == 0) {
          const uint32_t m = (marks >> (4 * (j0 & 7))) & 15;
          if (m != 0 && elect_one()) mbar_arrive(sb + B_P - 8 + 8 * m);
        }
#pragma unroll
        for (int hf = 0; hf < 2; hf++) {
#pragma unroll
          for (int i = hf * 8; i < hf * 8 + 8; i++) {
            if ((PMASK >> i) & 1) { p[2 * i] = exp_poly(s[2 * i], zero); p[2 * i + 1] = exp_poly(s[2 * i + 1], zero); }
            else { p[2 * i] = exp_mufu(s[2 * i]); p[2 * i + 1] = exp_mufu(s[2 * i + 1]); }
          }
          wg_fence();
#pragma unroll
          for (int i = hf * 4; i < hf * 4 + 4; i++) mma_pv(oh, p + 4 * i, dv[i]);
        }
        wg_commit();
#pragma unroll
        for (int i = 0; i < 8; i++) dv[i] = addlo_r(dv[i], inc);
      }
    wg_wait<0>();
    fence_u<6>(oh);
#pragma unroll
    for (int i = 0; i < 6; i++) { const float2 v = __half22float2(*(__half2*)&oh[i]); o[2 * i] += v.x; o[2 * i + 1] += v.y; }
    TQ(2 * jj);
    const int tid = fresh_tid(), bid = fresh_bid(), lane = tid & 31, g = lane >> 2, t = lane & 3;
    const int wg = __shfl_sync(~0u, tid >> 7, 0), wp = __shfl_sync(~0u, (tid >> 5) & 3, 0);
    const int h = bid >> 2, part = bid & 3, odd = h & 1, rloc = wg * 128 + wp * 16 + g;
    const float* gate = (const float*)(sm + SM_GATE) + rloc;
    const int src = (lane & ~3) | (odd ? 0 : 2);
    if ((jj & 7) == 7) {
      if (lane == 0 && wp == 0) TS(1, 16 + (jj >> 3) * 8 + wg);
      const float l0 = __shfl_sync(~0u, o[8], src), l1 = __shfl_sync(~0u, o[10], src);
      float chk = 0.f;
#pragma unroll
      for (int i = 0; i < 12; i++) chk += fabsf(o[i]);
      volatile uint32_t* flag = (volatile uint32_t*)(sm + SM_FLAG) + wg * 8 + (jj >> 3) * 4 + wp;
      const bool ok = *flag == 0 && l0 >= 64.f && l1 >= 64.f && chk < 1e30f;
      if (!__all_sync(~0u, ok)) { if (lane == 0) *flag = 1; }
      else {
        const float r0 = __fdividef(1.f - gate[(jj >> 3) * 64], l0), r1 = __fdividef(1.f - gate[(jj >> 3) * 64 + 8], l1);
        uint32_t v[6];
#pragma unroll
        for (int c = 0; c < 3; c++) { v[2 * c] = pack_b(o[4 * c] * r0, o[4 * c + 1] * r0); v[2 * c + 1] = pack_b(o[4 * c + 2] * r1, o[4 * c + 3] * r1); }
        store_o(v, 80, h, part * 512 + rloc + (jj >> 3) * 64, t);
      }
#pragma unroll
      for (int i = 0; i < 12; i++) o[i] = 0.f;
    } else {
      mbar_wait(sb + B_AQ, 0);
      const uint32_t kvi = (sl + SM_KVI) >> 4, img = (sl + SM_AQ + wg * SLICE) >> 4;
      mbar_wait(sb + B_KD, 0);
#pragma unroll 1
      for (int tl = 0; tl < 2; tl++) {
        float n[24];
        uint32_t e[12], v[6];
        float d[12];
        wg_fence();
        phi_logits(d, img + 64 * tl, (sl + SM_WPHI) >> 4);
        wg_commit();
        wg_wait<0>();
        phi_exp(e, d, t, zero);
        wg_fence();
        mma_b48_rs0(n, e, mkdesc(kvi, 768, 128, 0));
        mma_b48_rs(n, e + 4, mkdesc(kvi + 96, 768, 128, 0));
        mma_b48_rs(n, e + 8, mkdesc(kvi + 144, 768, 128, 0));
        wg_commit();
        wg_wait<0>();
        phi_out(v, n, gate + tl * 64, src);
        store_o(v, 0, h, part * 512 + rloc + tl * 64, t);
      }
      __syncwarp();
      if (lane == 0) mbar_arrive(sb + B_QD);
    }
    __syncwarp();
    TQ(2 * jj + 1);
  }
  bar_sync(8, 512);
  TQ(33);
  {
    const int tid = fresh_tid(), bid = fresh_bid(), lane = tid & 31;
    const int wg = __shfl_sync(~0u, tid >> 7, 0), wp = __shfl_sync(~0u, (tid >> 5) & 3, 0);
    if (__any_sync(~0u, ((const uint32_t*)(sm + SM_FLAG))[lane] != 0)) attn_fallback((const uint32_t*)(sm + SM_FLAG), bid >> 2, bid & 3, P.x, P.wB);
    if (tid == 384) { signal(C_OB + bid * 8); TS(2, 0); }
    if (wg == 2 && tid < 264) mbar_arrive_cluster(sb + B_OE + 48 + (tid & 2) * 4, tid & 1);
    if (wg < 2) {
      float acc[40];
#pragma unroll 1
      for (int it = 0; it < 20; it++) {
        const int s = it & 7;
        bool rel = it > 0 && it <= 12;
        if (!mbar_test_wg(sb + B_OF + 8 * s, (it >> 3) & 1, 4 + wg)) {
          wg_wait<0>();
          if (rel && (tid & 127) < 2) mbar_arrive_cluster(sb + B_OE + 8 * ((it - 1) & 7), tid & 1);
          rel = false;
          mbar_wait(sb + B_OF + 8 * s, (it >> 3) & 1);
        }
        if (tid == 0 && (it == 0 || it == 10)) TS(2, 2 + (it == 10));
        const uint32_t aa = (sl + o_slot(s) + wg * 1024) >> 4, wa = (sl + o_slot(s) + O_AB) >> 4;
        wg_fence();
#pragma unroll
        for (int k = 0; k < 4; k++) mma_n80(acc, mkdesc(aa + 256 * k, 2048, 128, 0), mkdesc(wa + 160 * k, 1280, 128, 0), (it | k) != 0);
        wg_commit();
        wg_wait<1>();
        if (rel && (tid & 127) < 2) mbar_arrive_cluster(sb + B_OE + 8 * ((it - 1) & 7), tid & 1);
      }
      wg_wait<0>();
      fence_f<40>(acc);
      if (tid == 0) TS(2, 4);
      TQ(36);
      const uint32_t stg = sb + o_slot(6) + wg * 10240;
      const uint32_t ad = stg + (wp * 16 + ((lane >> 3) & 1) * 8 + (lane & 7)) * 160 + (lane >> 4) * 16;
      bar_sync(1, 256);
#pragma unroll
      for (int i = 0; i < 5; i++)
        stsm4(ad + i * 32, pack_b(acc[8 * i], acc[8 * i + 1]), pack_b(acc[8 * i + 2], acc[8 * i + 3]), pack_b(acc[8 * i + 4], acc[8 * i + 5]), pack_b(acc[8 * i + 6], acc[8 * i + 7]));
      fence_async();
      bar_sync(4 + wg, 128);
      if ((tid & 127) == 0) {
        tma2d_store(&P.tmOut, stg, (bid & 7) * 80, (bid >> 3) * 128 + wg * 64);
        bulk_commit();
        asm volatile("cp.async.bulk.wait_group.read 0;" ::: "memory");
        if (tid == 0) TS(2, 5);
      }
    }
  }
  TQ(37);
}

typedef CUresult (*EncodeFn)(CUtensorMap*, CUtensorMapDataType, cuuint32_t, void*, const cuuint64_t*, const cuuint64_t*, const cuuint32_t*,
                             const cuuint32_t*, CUtensorMapInterleave, CUtensorMapSwizzle, CUtensorMapL2promotion, CUtensorMapFloatOOBfill);

void encode(EncodeFn fn, CUtensorMap* m, const void* p, int rank, const cuuint64_t* dims, const cuuint64_t* strides, const cuuint32_t* box, CUtensorMapSwizzle swz) {
  const cuuint32_t es[3] = {1, 1, 1};
  CUresult r = fn(m, CU_TENSOR_MAP_DATA_TYPE_BFLOAT16, rank, const_cast<void*>(p), dims, strides, box, es, CU_TENSOR_MAP_INTERLEAVE_NONE, swz,
                  CU_TENSOR_MAP_L2_PROMOTION_L2_256B, CU_TENSOR_MAP_FLOAT_OOB_FILL_NONE);
  if (r != CUDA_SUCCESS) fprintf(stderr, "tensor map encode failed: %d\n", (int)r);
}

}

extern "C" void kernel_launch(void* const* d_in, const int* in_sizes, int n_in, void* d_out, int out_size) {
  (void)in_sizes; (void)n_in; (void)out_size;
  static EncodeFn fn = nullptr;
  if (!fn) {
    void* p = nullptr;
    cudaDriverEntryPointQueryResult qr;
    cudaGetDriverEntryPoint("cuTensorMapEncodeTiled", &p, cudaEnableDefault, &qr);
    fn = (EncodeFn)p;
    cudaFuncSetAttribute(fused_kernel, cudaFuncAttributeMaxDynamicSharedMemorySize, SM_TOTAL);
  }
  Params P;
  P.x = (const __nv_bfloat16*)d_in[0];
  P.w_phi = (const __nv_bfloat16*)d_in[2];
  P.wB = (const __nv_bfloat16*)d_in[5];
  P.gate_w = (const __nv_bfloat16*)d_in[7];
  P.wA = (const __nv_bfloat16*)d_in[1];
  P.woA = (const __nv_bfloat16*)d_in[3];
  P.woB = (const __nv_bfloat16*)d_in[6];
  {
    const cuuint64_t d[2] = {640, 2048}, st[1] = {1280};
    const cuuint32_t box[2] = {64, 128}, obox[2] = {80, 64};
    encode(fn, &P.tmX, d_in[0], 2, d, st, box, CU_TENSOR_MAP_SWIZZLE_128B);
    encode(fn, &P.tmOut, d_out, 2, d, st, obox, CU_TENSOR_MAP_SWIZZLE_NONE);
  }
  {
    const cuuint64_t d[2] = {1920, 640}, st[1] = {3840};
    const cuuint32_t box[2] = {64, 32};
    encode(fn, &P.tmWA, d_in[1], 2, d, st, box, CU_TENSOR_MAP_SWIZZLE_128B);
    encode(fn, &P.tmWB, d_in[5], 2, d, st, box, CU_TENSOR_MAP_SWIZZLE_128B);
  }
  fused_kernel<<<128, 640, SM_TOTAL, cudaStreamPerThread>>>(P);
}
```

```cpp
#include <cuda_runtime.h>
#include <cuda_bf16.h>
#include <cuda_fp16.h>
#include <cuda.h>
#include <stdint.h>
#include <stdio.h>


namespace {

constexpr int S_ = 2048, D_ = 640, H_ = 32;
constexpr int SLICE = 6144;
constexpr int KVB = 2 * SLICE;
constexpr uint32_t PMASK = 0xADADu;
constexpr float QSCALE = 0.32259642f;

__device__ __align__(1024) uint8_t g_qB[H_ * 16 * SLICE];
__device__ __align__(1024) uint8_t g_kvB[H_ * 16 * KVB];
__device__ __align__(1024) uint8_t g_A[3 * H_ * 16 * SLICE];
__device__ __align__(1024) uint8_t g_o[16 * 160 * 2048];
__device__ __align__(1024) uint8_t g_wo[8 * 20 * 10240];
__device__ __align__(128) float g_stat[H_ * 32];
__device__ __align__(16) float g_gate[S_];
__device__ __align__(16) float g_kvs[H_ * 40 * 24];
__device__ __align__(16) __nv_bfloat16 g_fb[H_ * S_ * 40];
constexpr int C_B = 0, C_EXIT = 64, C_OA = 96, C_KV = 224, C_A = C_KV + 32 * 32, C_OB = C_A + 4, C_N = C_A + 128 * 8;
__device__ __align__(128) unsigned int g_cnt[C_N];

__device__ __forceinline__ uint32_t smem_u32(const void* p) { return (uint32_t)__cvta_generic_to_shared(p); }
__device__ __forceinline__ uint64_t mkdesc(uint32_t a16, uint32_t lbo, uint32_t sbo, uint32_t swz) {
  uint32_t lo = a16 + ((lbo >> 4) << 16);
  uint32_t hi = (sbo >> 4) | (swz << 30);
  return ((uint64_t)hi << 32) | lo;
}
__device__ __forceinline__ uint64_t addlo_r(uint64_t d, uint32_t inc) {
  asm volatile("{.reg .b32 lo, hi; mov.b64 {lo,hi}, %0; add.u32 lo, lo, %1; mov.b64 %0, {lo,hi};}" : "+l"(d) : "r"(inc));
  return d;
}
__device__ __forceinline__ void wg_fence() { asm volatile("wgmma.fence.sync.aligned;" ::: "memory"); }
__device__ __forceinline__ void wg_commit() { asm volatile("wgmma.commit_group.sync.aligned;" ::: "memory"); }
template <int N> __device__ __forceinline__ void wg_wait() { asm volatile("wgmma.wait_group.sync.aligned %0;" ::"n"(N) : "memory"); }
template <int N> __device__ __forceinline__ void fence_f(float* r) {
#pragma unroll
  for (int i = 0; i < N; i++) asm volatile("" : "+f"(r[i])::"memory");
}
template <int N> __device__ __forceinline__ void fence_u(uint32_t* r) {
#pragma unroll
  for (int i = 0; i < N; i++) asm volatile("" : "+r"(r[i])::"memory");
}
__device__ __forceinline__ void mbar_init(uint32_t bar, uint32_t cnt) { asm volatile("mbarrier.init.shared::cta.b64 [%0], %1;" ::"r"(bar), "r"(cnt) : "memory"); }
__device__ __forceinline__ void mbar_expect_tx(uint32_t bar, uint32_t bytes) { asm volatile("mbarrier.arrive.expect_tx.shared::cta.b64 _, [%0], %1;" ::"r"(bar), "r"(bytes) : "memory"); }
__device__ __forceinline__ void mbar_wait(uint32_t bar, uint32_t parity) {
  asm volatile(
      "{\n.reg .pred p;\n.reg .u32 n;\nmov.u32 n, 0;\n"
      "W: mbarrier.try_wait.parity.shared::cta.b64 p, [%0], %1;\n@p bra D;\n"
      "add.u32 n, n, 1;\nsetp.lt.u32 p, n, 0x1000000;\n@p bra W;\ntrap;\nD:\n}" ::"r"(bar), "r"(parity) : "memory");
}
__device__ __forceinline__ bool mbar_test_wg(uint32_t bar, uint32_t parity, int id) {
  uint32_t r;
  asm volatile("{.reg .pred p, q; mbarrier.test_wait.parity.shared::cta.b64 p, [%1], %2; bar.red.and.pred q, %3, 128, p; selp.u32 %0, 1, 0, q;}"
               : "=r"(r) : "r"(bar), "r"(parity), "r"(id) : "memory");
  return r != 0;
}
__device__ __forceinline__ void mbar_wait_z(uint32_t bar, uint32_t parity) {
  asm volatile(
      "{\n.reg .pred p;\n.reg .u32 n;\nmov.u32 n, 0;\n"
      "W: mbarrier.try_wait.parity.shared::cta.b64 p, [%0], %1, 20000;\n@p bra D;\n"
      "add.u32 n, n, 1;\nsetp.lt.u32 p, n, 0x100000;\n@p bra W;\ntrap;\nD:\n}" ::"r"(bar), "r"(parity) : "memory");
}
__device__ __forceinline__ void mbar_wait_u(uint32_t bar, uint32_t parity) {
  asm volatile("{\n.reg .pred p;\nW: mbarrier.try_wait.parity.shared::cta.b64 p, [%0], %1;\n@p bra D;\nbra W;\nD:\n}" ::"r"(bar), "r"(parity) : "memory");
}
__device__ __forceinline__ void mbar_arrive_cluster(uint32_t bar, uint32_t cta) {
  asm volatile("{.reg .b32 r; mapa.shared::cluster.u32 r, %0, %1; mbarrier.arrive.shared::cluster.b64 _, [r];}" ::"r"(bar), "r"(cta) : "memory");
}
__device__ __forceinline__ void bulk_g2s(uint32_t dst, const void* src, uint32_t bytes, uint32_t bar) {
  asm volatile("cp.async.bulk.shared::cluster.global.mbarrier::complete_tx::bytes [%0], [%1], %2, [%3];" ::"r"(dst), "l"(src), "r"(bytes), "r"(bar) : "memory");
}
__device__ __forceinline__ void bulk_g2s_mc(uint32_t dst, const void* src, uint32_t bytes, uint32_t bar, uint16_t mask) {
  asm volatile("cp.async.bulk.shared::cluster.global.mbarrier::complete_tx::bytes.multicast::cluster [%0], [%1], %2, [%3], %4;" ::"r"(dst), "l"(src), "r"(bytes), "r"(bar), "h"(mask) : "memory");
}
__device__ __forceinline__ void bulk_s2g(void* dst, uint32_t src, uint32_t bytes) {
  asm volatile("cp.async.bulk.global.shared::cta.bulk_group [%0], [%1], %2;" ::"l"(dst), "r"(src), "r"(bytes) : "memory");
}
__device__ __forceinline__ void tma2d(uint32_t dst, const CUtensorMap* m, int c0, int c1, uint32_t bar) {
  asm volatile("cp.async.bulk.tensor.2d.shared::cluster.global.mbarrier::complete_tx::bytes [%0], [%1, {%3, %4}], [%2];" ::"r"(dst), "l"(m), "r"(bar), "r"(c0), "r"(c1) : "memory");
}
__device__ __forceinline__ void tma2d_mc(uint32_t dst, const CUtensorMap* m, int c0, int c1, uint32_t bar, uint16_t mask) {
  asm volatile("cp.async.bulk.tensor.2d.shared::cluster.global.mbarrier::complete_tx::bytes.multicast::cluster [%0], [%1, {%3, %4}], [%2], %5;" ::"r"(dst), "l"(m), "r"(bar), "r"(c0), "r"(c1), "h"(mask) : "memory");
}
__device__ __forceinline__ void tma2d_store(const CUtensorMap* m, uint32_t src, int c0, int c1) {
  asm volatile("cp.async.bulk.tensor.2d.global.shared::cta.bulk_group [%0, {%2, %3}], [%1];" ::"l"(m), "r"(src), "r"(c0), "r"(c1) : "memory");
}
__device__ __forceinline__ void bulk_commit() { asm volatile("cp.async.bulk.commit_group;" ::: "memory"); }
__device__ __forceinline__ void bulk_wait_all() { asm volatile("cp.async.bulk.wait_group 0;" ::: "memory"); }
__device__ __forceinline__ void fence_async() { asm volatile("fence.proxy.async.shared::cta;" ::: "memory"); }
__device__ __forceinline__ void bar_sync(int id, int n) { asm volatile("bar.sync %0, %1;" ::"r"(id), "r"(n) : "memory"); }
__device__ __forceinline__ void bar_arrive(int id, int n) { asm volatile("bar.arrive %0, %1;" ::"r"(id), "r"(n) : "memory"); }
__device__ __forceinline__ void mbar_arrive(uint32_t bar) { asm volatile("mbarrier.arrive.shared::cta.b64 _, [%0];" ::"r"(bar) : "memory"); }
__device__ __forceinline__ void fence_gpu() { asm volatile("fence.acq_rel.gpu;" ::: "memory"); }
__device__ __forceinline__ void fence_async_g() { asm volatile("fence.proxy.async.global;" ::: "memory"); }
__device__ __forceinline__ void signal(int c) { fence_gpu(); asm volatile("red.relaxed.gpu.global.add.u32 [%0], 1;" ::"l"(g_cnt + c) : "memory"); }
__device__ __forceinline__ void await(int c, uint32_t target) {
  asm volatile(
      "{\n.reg .pred p;\n.reg .u32 n, v;\nmov.u32 n, 0;\n"
      "W: ld.acquire.gpu.global.u32 v, [%0];\nsetp.ge.u32 p, v, %1;\n@p bra D;\n"
      "nanosleep.u32 64;\nadd.u32 n, n, 1;\nsetp.lt.u32 p, n, 0x400000;\n@p bra W;\ntrap;\nD:\n}" ::"l"(g_cnt + c), "r"(target) : "memory");
}
__device__ __forceinline__ void await_all(int c, uint32_t target) {
  asm volatile(
      "{\n.reg .pred p;\n.reg .u32 n, v;\nmov.u32 n, 0;\n"
      "W: ld.acquire.gpu.global.u32 v, [%0];\nsetp.ge.u32 p, v, %1;\nvote.sync.all.pred p, p, 0xffffffff;\n@p bra.uni D;\n"
      "nanosleep.u32 64;\nadd.u32 n, n, 1;\nsetp.lt.u32 p, n, 0x400000;\n@p bra.uni W;\ntrap;\nD:\n}" ::"l"(g_cnt + c), "r"(target) : "memory");
}
__device__ __forceinline__ uint32_t await_mask(int c, uint32_t need) {
  uint32_t m;
  asm volatile(
      "{\n.reg .pred p;\n.reg .u32 n, v;\nmov.u32 n, 0;\n"
      "W: ld.acquire.gpu.global.u32 v, [%1];\nsetp.ne.u32 p, v, 0;\nvote.sync.ballot.b32 %0, p, 0xffffffff;\n"
      "and.b32 v, %0, %2;\nsetp.eq.u32 p, v, %2;\n@p bra.uni D;\n"
      "add.u32 n, n, 1;\nsetp.lt.u32 p, n, 0x400000;\n@p bra.uni W;\ntrap;\nD:\n}" : "=r"(m) : "l"(g_cnt + c), "r"(need) : "memory");
  return m;
}
__device__ __forceinline__ bool elect_one() {
  uint32_t p;
  asm volatile("{.reg .pred p; elect.sync _|p, 0xffffffff; selp.u32 %0, 1, 0, p;}" : "=r"(p));
  return p != 0;
}
__device__ __forceinline__ int fresh_tid() { int v; asm volatile("mov.u32 %0, %%tid.x;" : "=r"(v)); return v < 128 ? v + 512 : v - 128; }
__device__ __forceinline__ int fresh_bid() { int v; asm volatile("mov.u32 %0, %%ctaid.x;" : "=r"(v)); return v; }
__device__ __forceinline__ void stsm2(uint32_t addr, uint32_t a, uint32_t b) {
  asm volatile("stmatrix.sync.aligned.m8n8.x2.shared.b16 [%0], {%1,%2};" ::"r"(addr), "r"(a), "r"(b) : "memory");
}
__device__ __forceinline__ uint4 lds128(uint32_t a) { uint4 v; asm volatile("ld.shared.v4.u32 {%0,%1,%2,%3}, [%4];" : "=r"(v.x), "=r"(v.y), "=r"(v.z), "=r"(v.w) : "r"(a) : "memory"); return v; }
__device__ __forceinline__ void stsm4(uint32_t addr, uint32_t a, uint32_t b, uint32_t c, uint32_t d) {
  asm volatile("stmatrix.sync.aligned.m8n8.x4.shared.b16 [%0], {%1,%2,%3,%4};" ::"r"(addr), "r"(a), "r"(b), "r"(c), "r"(d) : "memory");
}
__device__ __forceinline__ uint32_t pack_h(float lo, float hi) { uint32_t r; asm("cvt.rn.f16x2.f32 %0, %1, %2;" : "=r"(r) : "f"(hi), "f"(lo)); return r; }
__device__ __forceinline__ uint32_t pack_b(float lo, float hi) { uint32_t r; asm("cvt.rn.bf16x2.f32 %0, %1, %2;" : "=r"(r) : "f"(hi), "f"(lo)); return r; }
__device__ __forceinline__ float ex2f(float x) { float r; asm("ex2.approx.ftz.f32 %0, %1;" : "=f"(r) : "f"(x)); return r; }
__device__ __forceinline__ float bf_lo(uint32_t u) { return __uint_as_float(u << 16); }
__device__ __forceinline__ float bf_hi(uint32_t u) { return __uint_as_float(u & 0xffff0000u); }

#define F4(o) "+f"(d[o + 0]), "+f"(d[o + 1]), "+f"(d[o + 2]), "+f"(d[o + 3])
#define F8(o) F4(o), F4(o + 4)
#define F40(o) F8(o), F8(o + 8), F8(o + 16), F8(o + 24), F8(o + 32)
#define RU8(o) "+r"(d[o + 0]), "+r"(d[o + 1]), "+r"(d[o + 2]), "+r"(d[o + 3]), "+r"(d[o + 4]), "+r"(d[o + 5]), "+r"(d[o + 6]), "+r"(d[o + 7])
#define WU8(o) "=r"(d[o + 0]), "=r"(d[o + 1]), "=r"(d[o + 2]), "=r"(d[o + 3]), "=r"(d[o + 4]), "=r"(d[o + 5]), "=r"(d[o + 6]), "=r"(d[o + 7])
#define A4 "r"(a[0]), "r"(a[1]), "r"(a[2]), "r"(a[3])

__device__ __forceinline__ void mma_n128(float* d, uint64_t a, uint64_t b, int acc) {
  asm volatile(
      "{.reg .pred p; setp.ne.b32 p, %66, 0;\n"
      "wgmma.mma_async.sync.aligned.m64n128k16.f32.bf16.bf16 {"
      "%0,%1,%2,%3,%4,%5,%6,%7,%8,%9,%10,%11,%12,%13,%14,%15,%16,%17,%18,%19,%20,%21,%22,%23,"
      "%24,%25,%26,%27,%28,%29,%30,%31,%32,%33,%34,%35,%36,%37,%38,%39,%40,%41,%42,%43,%44,%45,%46,%47,"
      "%48,%49,%50,%51,%52,%53,%54,%55,%56,%57,%58,%59,%60,%61,%62,%63"
      "}, %64, %65, p, 1, 1, 0, 1;}"
      : F40(0), F8(40), F8(48), F8(56)
      : "l"(a), "l"(b), "r"(acc));
}
__device__ __forceinline__ void mma_n112(float* d, uint64_t a, uint64_t b, int acc) {
  asm volatile(
      "{.reg .pred p; setp.ne.b32 p, %58, 0;\n"
      "wgmma.mma_async.sync.aligned.m64n112k16.f32.bf16.bf16 {"
      "%0,%1,%2,%3,%4,%5,%6,%7,%8,%9,%10,%11,%12,%13,%14,%15,%16,%17,%18,%19,%20,%21,%22,%23,"
      "%24,%25,%26,%27,%28,%29,%30,%31,%32,%33,%34,%35,%36,%37,%38,%39,%40,%41,%42,%43,%44,%45,%46,%47,"
      "%48,%49,%50,%51,%52,%53,%54,%55"
      "}, %56, %57, p, 1, 1, 0, 1;}"
      : F40(0), F8(40), F8(48)
      : "l"(a), "l"(b), "r"(acc));
}
__device__ __forceinline__ void mma_n80(float* d, uint64_t a, uint64_t b, int acc) {
  asm volatile(
      "{.reg .pred p; setp.ne.b32 p, %42, 0;\n"
      "wgmma.mma_async.sync.aligned.m64n80k16.f32.bf16.bf16 {"
      "%0,%1,%2,%3,%4,%5,%6,%7,%8,%9,%10,%11,%12,%13,%14,%15,%16,%17,%18,%19,%20,%21,%22,%23,%24,%25,%26,%27,%28,%29,"
      "%30,%31,%32,%33,%34,%35,%36,%37,%38,%39}, %40, %41, p, 1, 1, 0, 1;}"
      : F40(0)
      : "l"(a), "l"(b), "r"(acc));
}
__device__ __forceinline__ void mma_qk_first(uint32_t* d, uint64_t a, uint64_t b) {
  asm volatile(
      "wgmma.mma_async.sync.aligned.m64n128k16.f16.f16.f16 {%0,%1,%2,%3,%4,%5,%6,%7,%8,%9,%10,%11,%12,%13,%14,%15,%16,%17,%18,%19,%20,%21,%22,%23,%24,%25,%26,%27,%28,%29,%30,%31}, %32, %33, 0, 1, 1, 0, 0;"
      : WU8(0), WU8(8), WU8(16), WU8(24)
      : "l"(a), "l"(b));
}
__device__ __forceinline__ void mma_qk_acc(uint32_t* d, uint64_t a, uint64_t b) {
  asm volatile(
      "wgmma.mma_async.sync.aligned.m64n128k16.f16.f16.f16 {%0,%1,%2,%3,%4,%5,%6,%7,%8,%9,%10,%11,%12,%13,%14,%15,%16,%17,%18,%19,%20,%21,%22,%23,%24,%25,%26,%27,%28,%29,%30,%31}, %32, %33, 1, 1, 1, 0, 0;"
      : RU8(0), RU8(8), RU8(16), RU8(24)
      : "l"(a), "l"(b));
}
__device__ __forceinline__ void mma_pv(uint32_t* d, const uint32_t* a, uint64_t b) {
  asm volatile("wgmma.mma_async.sync.aligned.m64n24k16.f16.f16.f16 {%0,%1,%2,%3,%4,%5}, {%6,%7,%8,%9}, %10, 1, 1, 1, 1;"
               : "+r"(d[0]), "+r"(d[1]), "+r"(d[2]), "+r"(d[3]), "+r"(d[4]), "+r"(d[5])
               : A4, "l"(b));
}
#define W4(o) "=f"(d[o + 0]), "=f"(d[o + 1]), "=f"(d[o + 2]), "=f"(d[o + 3])
__device__ __forceinline__ void mma_b48_rs0(float* d, const uint32_t* a, uint64_t b) {
  asm volatile("wgmma.mma_async.sync.aligned.m64n48k16.f32.bf16.bf16 {%0,%1,%2,%3,%4,%5,%6,%7,%8,%9,%10,%11,%12,%13,%14,%15,%16,%17,%18,%19,%20,%21,%22,%23}, {%24,%25,%26,%27}, %28, 0, 1, 1, 0;"
               : W4(0), W4(4), W4(8), W4(12), W4(16), W4(20)
               : A4, "l"(b));
}
__device__ __forceinline__ void mma_b48_rs(float* d, const uint32_t* a, uint64_t b) {
  asm volatile("wgmma.mma_async.sync.aligned.m64n48k16.f32.bf16.bf16 {%0,%1,%2,%3,%4,%5,%6,%7,%8,%9,%10,%11,%12,%13,%14,%15,%16,%17,%18,%19,%20,%21,%22,%23}, {%24,%25,%26,%27}, %28, 1, 1, 1, 0;"
               : F8(0), F8(8), F8(16)
               : A4, "l"(b));
}
__device__ __forceinline__ void mma_b8_rs0(float* d, const uint32_t* a, uint64_t b) {
  asm volatile("wgmma.mma_async.sync.aligned.m64n8k16.f32.bf16.bf16 {%0,%1,%2,%3}, {%4,%5,%6,%7}, %8, 0, 1, 1, 0;" : W4(0) : A4, "l"(b));
}
__device__ __forceinline__ void mma_b8_rs(float* d, const uint32_t* a, uint64_t b) {
  asm volatile("wgmma.mma_async.sync.aligned.m64n8k16.f32.bf16.bf16 {%0,%1,%2,%3}, {%4,%5,%6,%7}, %8, 1, 1, 1, 0;" : F4(0) : A4, "l"(b));
}
__device__ __forceinline__ uint32_t mul_b2(uint32_t a, uint32_t b) { uint32_t r; asm("mul.rn.bf16x2 %0, %1, %2;" : "=r"(r) : "r"(a), "r"(b)); return r; }
__device__ __forceinline__ void mma_b24_ss0(float* d, uint64_t a, uint64_t b) {
  asm volatile("wgmma.mma_async.sync.aligned.m64n24k16.f32.bf16.bf16 {%0,%1,%2,%3,%4,%5,%6,%7,%8,%9,%10,%11}, %12, %13, 0, 1, 1, 0, 0;"
               : W4(0), W4(4), W4(8)
               : "l"(a), "l"(b));
}
__device__ __forceinline__ void mma_b24_ss(float* d, uint64_t a, uint64_t b) {
  asm volatile("wgmma.mma_async.sync.aligned.m64n24k16.f32.bf16.bf16 {%0,%1,%2,%3,%4,%5,%6,%7,%8,%9,%10,%11}, %12, %13, 1, 1, 1, 0, 0;"
               : F4(0), F4(4), F4(8)
               : "l"(a), "l"(b));
}
__device__ __forceinline__ void mma_b24_tt0(float* d, uint64_t a, uint64_t b) {
  asm volatile("wgmma.mma_async.sync.aligned.m64n24k16.f32.bf16.bf16 {%0,%1,%2,%3,%4,%5,%6,%7,%8,%9,%10,%11}, %12, %13, 0, 1, 1, 1, 1;"
               : W4(0), W4(4), W4(8)
               : "l"(a), "l"(b));
}
__device__ __forceinline__ void mma_b24_tt(float* d, uint64_t a, uint64_t b) {
  asm volatile("wgmma.mma_async.sync.aligned.m64n24k16.f32.bf16.bf16 {%0,%1,%2,%3,%4,%5,%6,%7,%8,%9,%10,%11}, %12, %13, 1, 1, 1, 1, 1;"
               : F4(0), F4(4), F4(8)
               : "l"(a), "l"(b));
}

constexpr int G_XB = 16384, G_WB = 16384, G_PB = G_XB + 2 * G_WB;
constexpr int SM_STG = 3 * G_PB;
constexpr int SM_Q = 0, KV0 = 4 * SLICE;
constexpr int SM_PHI = KV0 + 4 * KVB;
constexpr int SM_AQ = KV0 + 14 * KVB;
constexpr int SM_MISC = SM_STG + 12 * SLICE;
constexpr int B_FULL = SM_MISC, B_EMPTY = B_FULL + 48, B_KV = B_EMPTY + 48, B_BD = B_KV + 256, B_QR = B_BD + 8, B_AV = B_QR + 8,
              B_AQ = B_AV + 8, B_KD = B_AQ + 8, B_QD = B_KD + 8, B_OF = B_QD + 8, B_OE = B_OF + 64, B_P = B_OE + 64;
constexpr int SM_FLAG = SM_MISC + 896;
constexpr int SM_WPHI = SM_MISC + 1024;
constexpr int SM_RED = SM_WPHI + 1536;
constexpr int SM_GATE = SM_RED + 256;
constexpr int SM_IND = SM_GATE + 2048;
constexpr int SM_KVI = SM_IND + 640;
constexpr int SM_ZERO = SM_KVI + 3840;
constexpr int SM_TOTAL = SM_ZERO + 1024;
constexpr int O_AB = 16384, O_WB = 10240, O_STB = O_AB + O_WB;
__host__ __device__ constexpr int o_slot(int i) { return SM_MISC - (i + 1) * O_STB; }

template <bool BR_B>
__device__ __forceinline__ void g_epilogue(float* acc, uint32_t stg, int ct, int w, int wp, int lane) {
  const int t = lane & 3, hf = (lane >> 3) & 1, csel = lane >> 4, r = lane & 7;
  const int Rw = w * 64 + wp * 16;
  const uint32_t offK = Rw * 16 + hf * 128 + r * 16, offV = (Rw / 8 + hf) * 384 + r * 16;
  const bool p0 = (PMASK >> (Rw / 8)) & 1, p1 = (PMASK >> (Rw / 8 + 1)) & 1;
  const bool lo = t < 2, ev = !(t & 1);
#pragma unroll
  for (int j = 0; j < 6; j++) {
    const int type = (ct * 12 + 2 * j) >> 5;
    float* a = acc + 20 * j;
    uint32_t aug0, aug1, q[10];
    if (BR_B) {
      const float s0 = type == 0 ? QSCALE : (type == 1 && p0) ? 0.001953125f : 1.f;
      const float s1 = type == 0 ? QSCALE : (type == 1 && p1) ? 0.001953125f : 1.f;
      aug0 = (type == 0 || !ev) ? 0u : (type == 1 && p0) ? 0x18001800u : 0x00003C00u;
      aug1 = (type == 0 || !ev) ? 0u : (type == 1 && p1) ? 0x18001800u : 0x00003C00u;
#pragma unroll
      for (int i = 0; i < 5; i++) { q[2 * i] = pack_h(a[4 * i] * s0, a[4 * i + 1] * s0); q[2 * i + 1] = pack_h(a[4 * i + 2] * s1, a[4 * i + 3] * s1); }
    } else {
      aug0 = aug1 = (type == 2 && ev) ? 0x00003F80u : 0u;
#pragma unroll
      for (int i = 0; i < 10; i++) q[i] = pack_b(a[2 * i], a[2 * i + 1]);
    }
    const uint32_t base = stg + 2 * j * SLICE + (type == 2 ? offV : offK);
    const uint32_t cs = type == 2 ? 128 : 2048;
    stsm4(base + csel * cs, q[0], q[1], q[2], q[3]);
    stsm4(base + 2 * cs + csel * SLICE, lo ? q[4] : aug0, lo ? q[5] : aug1, lo ? aug0 : q[4], lo ? aug1 : q[5]);
    stsm4(base + SLICE + csel * cs, q[6], q[7], q[8], q[9]);
  }
}

__device__ __forceinline__ uint32_t exp_mufu(uint32_t s) { uint32_t r; asm("ex2.approx.f16x2 %0, %1;" : "=r"(r) : "r"(s)); return r; }
__device__ __forceinline__ uint32_t hfma(uint32_t a, uint32_t b, uint32_t c) { uint32_t r; asm("fma.rn.f16x2 %0, %1, %2, %3;" : "=r"(r) : "r"(a), "r"(b), "r"(c)); return r; }
__device__ __forceinline__ uint32_t hfma_relu(uint32_t a, uint32_t b, uint32_t c) { uint32_t r; asm("fma.rn.relu.f16x2 %0, %1, %2, %3;" : "=r"(r) : "r"(a), "r"(b), "r"(c)); return r; }
#define D2(x) ((x) * 0x10001u)
__device__ __forceinline__ uint32_t exp_poly(uint32_t u, uint32_t zero) {
  uint32_t r = hfma_relu(u, D2(0x0200u), 0u);
  uint32_t f = hfma(r, D2(0xF800u), u);
  uint32_t w = hfma(f, D2(0x60fcu), D2(0x457fu));
  w = hfma(f, w, D2(0x27d8u));
  w = hfma_relu(f, w, D2(0x05a8u));
  return __funnelshift_l(zero, r, 10) + w;
}

__device__ __forceinline__ void phi_logits(float* d, uint32_t img16, uint32_t wphi16) {
  mma_b24_ss0(d, mkdesc(img16, 2048, 128, 0), mkdesc(wphi16, 384, 128, 0));
  mma_b24_ss(d, mkdesc(img16 + 128, 2048, 128, 0), mkdesc(wphi16 + 48, 384, 128, 0));
}
__device__ __forceinline__ void phi_exp(uint32_t* e, float* d, int t, uint32_t zero) {
  fence_f<12>(d);
#pragma unroll
  for (int i = 0; i < 12; i++) d[i] *= 1.4426950408889634f;
  const bool lo = t < 2;
  const uint32_t sgn = lo ? 0u : 0x80000000u;
#pragma unroll
  for (int hf = 0; hf < 2; hf++) {
    const float* x = d + 2 * hf;
    e[hf] = pack_b(ex2f(x[0]), ex2f(x[1])); e[2 + hf] = pack_b(ex2f(x[4]), ex2f(x[5]));
    e[4 + hf] = pack_b(ex2f(__uint_as_float(__float_as_uint(x[8]) ^ sgn)), ex2f(__uint_as_float(__float_as_uint(x[9]) ^ sgn)));
    e[6 + hf] = pack_b(ex2f(-x[0]), ex2f(-x[1])); e[10 + hf] = pack_b(ex2f(-x[4]), ex2f(-x[5]));
  }
  float am[3];
#pragma unroll
  for (int i = 0; i < 3; i++) am[i] = fmaxf(fmaxf(fabsf(d[4 * i]), fabsf(d[4 * i + 1])), fmaxf(fabsf(d[4 * i + 2]), fabsf(d[4 * i + 3])));
  if (!__all_sync(~0u, fmaxf(fmaxf(am[0], am[1]), am[2]) <= 40.f)) {
#pragma unroll
    for (int hf = 0; hf < 2; hf++) {
      const float* x = d + 2 * hf;
      float mx = fmaxf(fmaxf(fmaxf(x[0], x[1]), fmaxf(x[4], x[5])), fmaxf(x[8], x[9]));
      float mn = fminf(fminf(fminf(x[0], x[1]), fminf(x[4], x[5])), fminf(x[8], x[9]));
      mx = fmaxf(mx, __shfl_xor_sync(~0u, mx, 1)); mn = fminf(mn, __shfl_xor_sync(~0u, mn, 1));
      mx = fmaxf(mx, __shfl_xor_sync(~0u, mx, 2)); mn = fminf(mn, __shfl_xor_sync(~0u, mn, 2));
      e[hf] = pack_b(ex2f(x[0] - mx), ex2f(x[1] - mx)); e[2 + hf] = pack_b(ex2f(x[4] - mx), ex2f(x[5] - mx));
      e[4 + hf] = pack_b(ex2f(lo ? x[8] - mx : mn - x[8]), ex2f(lo ? x[9] - mx : mn - x[9]));
      e[6 + hf] = pack_b(ex2f(mn - x[0]), ex2f(mn - x[1])); e[10 + hf] = pack_b(ex2f(mn - x[4]), ex2f(mn - x[5]));
    }
  }
  e[8] = zero; e[9] = zero;
  fence_u<12>(e);
}

__device__ __forceinline__ void phi_out(uint32_t* v, float* d, const float* gate, int src) {
  fence_f<24>(d);
#pragma unroll
  for (int hf = 0; hf < 2; hf++) {
    const float rp = __fdividef(1.f, d[9 + 2 * hf]), rn = __fdividef(1.f, d[21 + 2 * hf]);
    const float sc = __fdividef(gate[8 * hf], fmaf(d[8 + 2 * hf], rp, fmaf(d[20 + 2 * hf], rn, 1e-6f)));
    const float a = __shfl_sync(~0u, rp * sc, src), b = __shfl_sync(~0u, rn * sc, src);
#pragma unroll
    for (int c = 0; c < 3; c++)
      v[2 * c + hf] = pack_b(fmaf(d[12 + 4 * c + 2 * hf], b, d[4 * c + 2 * hf] * a), fmaf(d[13 + 4 * c + 2 * hf], b, d[4 * c + 2 * hf + 1] * a));
  }
}

__device__ __forceinline__ void store_o(const uint32_t* v, int cbase, int h, int row, int t) {
  uint32_t* p = (uint32_t*)(g_o + ((row >> 7) * 160 + cbase + (h >> 1) * 5) * 2048 + (row & 127) * 16) + t;
  uint32_t* p0 = p + ((h & 1) ? 1536 : 0);
  p0[0] = v[0]; p0[32] = v[1]; p0[512] = v[2]; p0[544] = v[3];
  if ((t >> 1) == (h & 1)) { p[1024] = v[4]; p[1056] = v[5]; }
}

__device__ __noinline__ void attn_fallback(const uint32_t* flags, int h, int part, const __nv_bfloat16* x, const __nv_bfloat16* wB) {
  __nv_bfloat16* kv = g_fb + (size_t)h * S_ * 40;
  const int tid = fresh_tid() - 256;
  for (int i = tid; i < S_ * 40; i += 256) {
    const int tok = i / 40, c = i % 40;
    const __nv_bfloat16* xr = x + (size_t)tok * D_;
    const __nv_bfloat16* wc = wB + (c < 20 ? 640 + h * 20 + c : 1280 + h * 20 + c - 20);
    float acc = 0.f;
    for (int k = 0; k < D_; k++) acc += __bfloat162float(xr[k]) * __bfloat162float(wc[(size_t)k * 1920]);
    kv[i] = __float2bfloat16(acc);
  }
  bar_sync(12, 256);
  const int warp = tid >> 5, lane = tid & 31;
  for (int wt = warp; wt < 32; wt += 8) {
    if (!flags[wt]) continue;
    for (int rr = 0; rr < 16; rr++) {
      const int row = part * 512 + wt * 16 + rr;
      float qv = 0.f;
      if (lane < 20) {
        for (int k = 0; k < D_; k++) qv += __bfloat162float(x[(size_t)row * D_ + k]) * __bfloat162float(wB[(size_t)k * 1920 + h * 20 + lane]);
        qv = __bfloat162float(__float2bfloat16(qv));
      }
      float m = -INFINITY, l = 0.f, o[20];
#pragma unroll
      for (int d = 0; d < 20; d++) o[d] = 0.f;
      for (int j = lane; j < S_; j += 32) {
        float s = 0.f;
#pragma unroll
        for (int d = 0; d < 20; d++) s += __shfl_sync(~0u, qv, d) * __bfloat162float(kv[j * 40 + d]);
        s = __bfloat162float(__float2bfloat16(__bfloat162float(__float2bfloat16(s)) * 0.22360679775f)) * 1.4426950408889634f;
        const float mn = fmaxf(m, s), c = exp2f(m - mn), p = exp2f(s - mn);
        l = l * c + p;
#pragma unroll
        for (int d = 0; d < 20; d++) o[d] = o[d] * c + p * __bfloat162float(kv[j * 40 + 20 + d]);
        m = mn;
      }
      float mg = m;
#pragma unroll
      for (int of = 16; of; of >>= 1) mg = fmaxf(mg, __shfl_xor_sync(~0u, mg, of));
      const float c = exp2f(m - mg);
      l *= c;
#pragma unroll
      for (int of = 16; of; of >>= 1) l += __shfl_xor_sync(~0u, l, of);
      const float sc = (1.f - __ldcg(g_gate + row)) / l;
#pragma unroll
      for (int d = 0; d < 20; d++) {
        float v = o[d] * c;
#pragma unroll
        for (int of = 16; of; of >>= 1) v += __shfl_xor_sync(~0u, v, of);
        const int col = h * 20 + d;
        if (lane == 0) *(__nv_bfloat16*)(g_o + ((size_t)(row >> 7) * 160 + 80 + (col >> 3)) * 2048 + (row & 127) * 16 + (col & 7) * 2) = __float2bfloat16(v * sc);
      }
    }
  }
  bar_sync(12, 256);
}

__device__ __forceinline__ void prep_q(uint8_t* sm, uint32_t sb, int i, int odd) {
  const uint32_t st = ((const uint32_t*)(sm + SM_RED))[i & 31];
  const float kn2 = __uint_as_float(__reduce_max_sync(~0u, (i & 16) ? 0u : st)), vmx = __uint_as_float(__reduce_max_sync(~0u, (i & 16) ? st : 0u));
  const bool head_ok = kn2 <= 1048576.f && vmx <= 32768.f && vmx >= 0.00390625f;
#pragma unroll
  for (int u = 0; u < 2; u++) {
    const int row = i + 256 * u;
    const uint32_t ad = sb + SM_Q + (row >> 7) * SLICE + (row & 127) * 16;
    const uint4 c0 = lds128(ad), c1 = lds128(ad + 2048), c2 = lds128(ad + 4096);
    const uint32_t v[12] = {c0.x, c0.y, c0.z, c0.w, c1.x, c1.y, c1.z, c1.w, c2.x, c2.y, c2.z, c2.w};
    float n0 = 0.f, n1 = 0.f;
#pragma unroll
    for (int c = 0; c < 12; c++) { const float2 a = __half22float2(*(const __half2*)&v[c]); n0 = fmaf(a.x, a.x, n0); n1 = fmaf(a.y, a.y, n1); }
    n0 += n1;
    float r;
    asm("sqrt.approx.f32 %0, %1;" : "=f"(r) : "f"(n0 * kn2));
    const float b = r * 1.01f + 0.05f;
    *(uint32_t*)(sm + SM_Q + (row >> 7) * SLICE + 4096 + (row & 127) * 16 + (odd ? 0 : 8)) = pack_h(-fmaxf(0.f, ceilf(b * 8.f - 126.f) * 0.125f), 13.5f);
    if (!(head_ok && b <= 30.f && n0 <= 1048576.f)) ((volatile uint32_t*)(sm + SM_FLAG))[row >> 4] = 1;
  }
}

struct Params {
  CUtensorMap tmX, tmWB, tmWA, tmOut;
  const __nv_bfloat16 *x, *gate_w, *w_phi, *wB, *woA, *woB;
};

__device__ __forceinline__ void agent_g(const Params& P, uint32_t sb) {
  const int bid = blockIdx.x, rank = bid & 1, lane = threadIdx.x & 31;
  const int pr = bid >> 1, rt = (pr & 7) * 2 + rank, ct = pr >> 3, h = bid >> 2, part = bid & 3;
  asm volatile("barrier.cluster.wait.aligned;" ::: "memory");
  if (elect_one()) {
#pragma unroll
    for (int it = 0; it < 6; it++) {
      const int s = (it + 2) % 6;
      const uint32_t st = sb + (s >> 1) * G_PB + G_XB + (s & 1) * G_WB + rank * 8192, fb = sb + B_FULL + 8 * s;
      tma2d_mc(st, &P.tmWB, ct * 240 + rank * 128, it * 32, fb, 3);
      tma2d_mc(st + 4096, &P.tmWB, ct * 240 + rank * 128 + 64, it * 32, fb, 3);
    }
    asm volatile("prefetch.tensormap [%0];" ::"l"(&P.tmWA) : "memory");
  }
  {
    int s = 2, ph = 0;
#pragma unroll 1
    for (int it = 6; it < 40; it++) {
      const int kb = it >= 20 ? it - 20 : it;
      const uint32_t st = sb + (s >> 1) * G_PB + G_XB + (s & 1) * G_WB + rank * 8192, fb = sb + B_FULL + 8 * s;
      const CUtensorMap* wm = it >= 20 ? &P.tmWA : &P.tmWB;
      mbar_wait_z(sb + B_EMPTY + 8 * s, ph);
      if (elect_one()) {
        mbar_expect_tx(fb, (s & 1) ? G_WB : G_XB + G_WB);
        if (s & 1) tma2d(sb + (s >> 1) * G_PB, &P.tmX, (kb - 1) * 32, rt * 128, fb - 8);
        tma2d_mc(st, wm, ct * 240 + rank * 128, kb * 32, fb, 3);
        tma2d_mc(st + 4096, wm, ct * 240 + rank * 128 + 64, kb * 32, fb, 3);
      }
      if (s == 1) ph ^= 1;
      if (++s == 6) s = 0;
    }
  }
  const uint8_t* kvsrc = g_kvB + (size_t)h * 16 * KVB;
  await(C_B, 128);
  mbar_wait_z(sb + B_EMPTY + 8, 1);
  if (elect_one()) {
    fence_async_g();
    mbar_expect_tx(sb + B_BD, 4 * SLICE + 2048 + 128);
    bulk_g2s(sb + SM_Q, g_qB + ((size_t)h * 16 + part * 4) * SLICE, 4 * SLICE, sb + B_BD);
    bulk_g2s(sb + SM_RED, g_stat + h * 32, 128, sb + B_BD);
    bulk_g2s(sb + SM_GATE, g_gate + part * 512, 2048, sb + B_BD);
#pragma unroll
    for (int j = 0; j < 2; j++) { mbar_expect_tx(sb + B_KV + 8 * j, KVB); bulk_g2s(sb + KV0 + j * KVB, kvsrc + j * KVB, KVB, sb + B_KV + 8 * j); }
  }
#pragma unroll
  for (int q = 1; q < 3; q++) {
    mbar_wait_z(sb + B_EMPTY + 16 * q + 8, 0);
    if (elect_one()) {
#pragma unroll
      for (int j = 4 * q - 2; j < 4 * q + 2; j++) { mbar_expect_tx(sb + B_KV + 8 * j, KVB); bulk_g2s(sb + KV0 + j * KVB, kvsrc + j * KVB, KVB, sb + B_KV + 8 * j); }
    }
  }
  bar_sync(9, 288);
  if (lane == 0) {
#pragma unroll
    for (int q = 0; q < 12; q++) bulk_s2g(g_A + ((size_t)(ct * 12 + q) * 16 + rt) * SLICE, sb + SM_STG + q * SLICE, SLICE);
    bulk_commit();
    bulk_wait_all();
  }
  __syncwarp();
  if (elect_one()) {
#pragma unroll
    for (int j = 10; j < 16; j++) { mbar_expect_tx(sb + B_KV + 8 * j, KVB); bulk_g2s(sb + KV0 + j * KVB, kvsrc + j * KVB, KVB, sb + B_KV + 8 * j); }
  }
  if (lane == 0) signal(C_A + bid * 8);
  {
    const int l12 = lane % 12, c2 = ((l12 >> 2) * 32 + h) / 12, r2 = part * 4 + (l12 & 3);
    await_all(C_A + (((c2 * 8 + (r2 >> 1)) << 1) | (r2 & 1)) * 8, 1);
  }
  mbar_wait_z(sb + B_P + 16 * 2, 0);
  if (elect_one()) {
    fence_async_g();
    mbar_expect_tx(sb + B_AV, 8 * SLICE);
#pragma unroll
    for (int q = 0; q < 4; q++) {
      bulk_g2s(sb + KV0 + q * KVB + SLICE, g_A + ((size_t)(H_ + h) * 16 + part * 4 + q) * SLICE, SLICE, sb + B_AV);
      bulk_g2s(sb + KV0 + q * KVB, g_A + ((size_t)(2 * H_ + h) * 16 + part * 4 + q) * SLICE, SLICE, sb + B_AV);
    }
  }
  mbar_wait_z(sb + B_P + 16 * 3, 0);
}

__device__ __forceinline__ void branch_a(uint8_t* sm, uint32_t sb) {
  const int tid = fresh_tid(), bid = fresh_bid(), lane = tid & 31, g = lane >> 2, t = lane & 3;
  const int wp = __shfl_sync(~0u, (tid >> 5) & 3, 0), h = bid >> 2, part = bid & 3;
  const uint32_t sl = sb & 0x3FFFF, wphi16 = (sl + SM_WPHI) >> 4;
  const uint32_t zero = *(volatile uint32_t*)(sm + SM_ZERO);
  {
    const uint32_t ad = sb + SM_PHI + (wp * 2 + ((lane >> 3) & 1)) * 640 + (lane >> 4) * 128 + (lane & 7) * 16;
    const uint32_t ind16 = (sl + SM_IND) >> 4;
    float* dst = g_kvs + h * 960 + (wp * 16 + g) * 24 + 2 * t;
    mbar_wait_z(sb + B_AV, 0);
    float d[12];
    wg_fence();
    phi_logits(d, (sl + KV0 + SLICE) >> 4, wphi16);
    wg_commit();
    wg_wait<0>();
#pragma unroll 1
    for (int i = 0; i < 8; i++) {
      const uint32_t unit = sl + KV0 + (i >> 1) * KVB, buf = (i & 3) * 5120;
      {
        uint32_t e[12];
        phi_exp(e, d, t, zero);
        float z[4];
        const int nx = min(i + 1, 7);
        wg_fence();
        mma_b8_rs0(z, e, mkdesc(ind16, 128, 128, 0));
        mma_b8_rs(z, e + 4, mkdesc(ind16 + 16, 128, 128, 0));
        mma_b8_rs(z, e + 8, mkdesc(ind16 + 24, 128, 128, 0));
        phi_logits(d, (sl + KV0 + (nx >> 1) * KVB + SLICE + (nx & 1) * 1024) >> 4, wphi16);
        wg_commit();
        wg_wait<0>();
        fence_f<4>(z); fence_u<12>(e);
        uint32_t r[2];
#pragma unroll
        for (int hf = 0; hf < 2; hf++) r[hf] = __shfl_sync(~0u, pack_b(__fdividef(1.f, z[2 * hf]), __fdividef(1.f, z[2 * hf + 1])), lane & ~3);
        const uint32_t p0 = __byte_perm(r[0], 0, 0x1010), p1 = __byte_perm(r[1], 0, 0x1010), n0 = __byte_perm(r[0], 0, 0x3232), n1 = __byte_perm(r[1], 0, 0x3232);
        stsm4(ad + buf, mul_b2(e[0], p0), mul_b2(e[1], p1), mul_b2(e[2], p0), mul_b2(e[3], p1));
        stsm4(ad + buf + 256, mul_b2(e[4], t < 2 ? p0 : n0), mul_b2(e[5], t < 2 ? p1 : n1), mul_b2(e[6], n0), mul_b2(e[7], n1));
        stsm2(ad + buf + 512, mul_b2(e[10], n0), mul_b2(e[11], n1));
      }
      if ((i & 3) == 3) {
        fence_async();
        bar_sync(11, 128);
        float kv[12];
        wg_fence();
        mma_b24_tt0(kv, mkdesc((sl + SM_PHI) >> 4, 640, 128, 0), mkdesc((unit - KVB) >> 4, 384, 128, 0));
#pragma unroll
        for (int k = 1; k < 16; k++)
          mma_b24_tt(kv, mkdesc(((sl + SM_PHI) >> 4) + k * 80, 640, 128, 0), mkdesc(((unit - KVB + (k >> 3) * KVB) >> 4) + (k & 7) * 48, 384, 128, 0));
        wg_commit();
        wg_wait<0>();
        fence_f<12>(kv);
        if (wp < 3) {
#pragma unroll
          for (int c = 0; c < 3; c++) asm volatile("red.relaxed.gpu.global.add.v2.f32 [%0], {%1,%2};" ::"l"(dst + 8 * c), "f"(kv[4 * c]), "f"(kv[4 * c + 1]) : "memory");
        }
        if (wp < 2) {
#pragma unroll
          for (int c = 0; c < 3; c++) asm volatile("red.relaxed.gpu.global.add.v2.f32 [%0], {%1,%2};" ::"l"(dst + 192 + 8 * c), "f"(kv[4 * c + 2]), "f"(kv[4 * c + 3]) : "memory");
        }
        if (i == 3) bar_sync(11, 128);
      }
    }
    bar_sync(11, 128);
    if (tid == 608) signal(C_KV + h * 32);
    if (wp == 0) {
      if (elect_one()) {
        const uint8_t* kvsrc = g_kvB + (size_t)h * 16 * KVB;
#pragma unroll
        for (int j = 5; j >= 0; j--) { mbar_expect_tx(sb + B_KV + 248 - 8 * j, KVB); bulk_g2s(sb + KV0 + j * KVB, kvsrc + j * KVB, KVB, sb + B_KV + 248 - 8 * j); }
      }
      mbar_wait_z(sb + B_P + 16 * 9, 0);
      if (elect_one()) {
        mbar_expect_tx(sb + B_AQ, 4 * SLICE);
        bulk_g2s(sb + SM_AQ, g_A + ((size_t)h * 16 + part * 4) * SLICE, 4 * SLICE, sb + B_AQ);
      }
      await(C_KV + h * 32, 4);
    }
    bar_sync(11, 128);
  }
  const int zc = (h & 1) ? 16 : 20;
#pragma unroll
  for (int u = 0; u < 2; u++) {
    const int j = (tid & 127) + 128 * u, fc = j / 48, n = j % 48, dd = n % 24;
    if (j < 240) {
      const float* kvs = g_kvs + h * 960 + fc * 192 + dd;
      uint32_t w[4];
#pragma unroll
      for (int c = 0; c < 4; c++) w[c] = dd == zc + 1 ? 0x3F803F80u : pack_b(__ldcg(kvs + 48 * c), __ldcg(kvs + 48 * c + 24));
      const bool neg = n >= 24, k0 = (fc > 2) == neg, k1 = (fc > 1) == neg;
      *(uint4*)(sm + SM_KVI + j * 16) = make_uint4(k0 ? w[0] : 0u, k0 ? w[1] : 0u, k1 ? w[2] : 0u, k1 ? w[3] : 0u);
    }
  }
  fence_async();
  __syncwarp();
  if (lane == 0) mbar_arrive(sb + B_KD);
}

__device__ __forceinline__ void agent_t(uint32_t sb) {
  const int bid = fresh_bid(), rank = bid & 1, lane = fresh_tid() & 31, part = bid & 3;
  mbar_wait_z(sb + B_QD, 0);
  if (lane == 0) signal(C_OA + part * 32);
  const uint8_t* osrc = g_o + (size_t)(bid >> 3) * 160 * 2048;
  const uint8_t* wsrc = g_wo + (bid & 7) * 204800;
  await(C_OA + (bid >> 5) * 32, 32);
  mbar_wait_z(sb + B_P + 16 * 13, 0);
  if (elect_one()) {
    fence_async_g();
#pragma unroll
    for (int it = 0; it < 4; it++) {
      mbar_expect_tx(sb + B_OF + 8 * it, O_STB);
      bulk_g2s(sb + o_slot(it) + O_AB, wsrc + it * O_WB, O_WB, sb + B_OF + 8 * it);
      bulk_g2s(sb + o_slot(it), osrc + it * O_AB, O_AB, sb + B_OF + 8 * it);
    }
  }
  mbar_wait_z(sb + B_P + 16 * 15, 0);
  if (elect_one()) {
#pragma unroll
    for (int it = 4; it < 6; it++) {
      mbar_expect_tx(sb + B_OF + 8 * it, O_STB);
      bulk_g2s(sb + o_slot(it) + O_AB, wsrc + it * O_WB, O_WB, sb + B_OF + 8 * it);
      bulk_g2s(sb + o_slot(it), osrc + it * O_AB, O_AB, sb + B_OF + 8 * it);
    }
  }
#pragma unroll
  for (int it = 6; it < 13; it++) {
    const uint32_t st = sb + o_slot(it & 7), fb = sb + B_OF + 8 * (it & 7);
    mbar_wait_z(sb + B_OE + 8 * (it & 7), it >= 14);
    if (elect_one()) {
      mbar_expect_tx(fb, O_STB);
      if (it < 10) bulk_g2s_mc(st + rank * 8192, osrc + it * O_AB + rank * 8192, 8192, fb, 3);
      bulk_g2s(st + O_AB, wsrc + it * O_WB, O_WB, fb);
    }
  }
  const int ob = C_OB + (bid >> 5) * 8 + lane * 32;
  uint32_t ready = 0;
#pragma unroll
  for (int it = 10; it < 20; it++) {
    const uint32_t st = sb + o_slot(it & 7), fb = sb + B_OF + 8 * (it & 7);
    const int h0 = (it - 10) * 64 / 20, h1 = ((it - 10) * 64 + 63) / 20;
    const uint32_t need = (uint32_t)((2ull << h1) - (1ull << h0));
    if (it >= 13) {
      mbar_wait(sb + B_OE + 8 * (it & 7), it >= 14);
      if (elect_one()) { mbar_expect_tx(fb, O_STB); bulk_g2s(st + O_AB, wsrc + it * O_WB, O_WB, fb); }
    }
    if ((ready & need) != need) { ready = await_mask(ob, need); fence_async_g(); }
    if (elect_one()) {
      bulk_g2s_mc(st + rank * 8192, osrc + it * O_AB + rank * 8192, 8192, fb, 3);
    }
  }
  uint32_t v = 0;
  if (lane == 0) v = atomicAdd(&g_cnt[C_EXIT], 1u);
  if (__shfl_sync(~0u, v, 0) == 127u) {
    g_cnt[C_KV + 32 * lane] = 0;
    if (lane < 7) g_cnt[32 * lane] = 0;
#pragma unroll
    for (int i = 0; i < 4; i++) { g_cnt[C_A + 8 * (lane + 32 * i)] = 0; g_cnt[C_OB + 8 * (lane + 32 * i)] = 0; }
  }
}

__global__ void __cluster_dims__(2, 1, 1) __launch_bounds__(640, 1) fused_kernel(const __grid_constant__ Params P) {
  extern __shared__ __align__(1024) uint8_t sm[];
  const uint32_t sb = __shfl_sync(~0u, smem_u32(sm), 0), sl = sb & 0x3FFFF;
  const int tid = fresh_tid(), wg = __shfl_sync(~0u, tid >> 7, 0), wp = __shfl_sync(~0u, (tid >> 5) & 3, 0), lane = tid & 31;
  const int bid = blockIdx.x;
  if (wg == 4 && wp == 0) {
    if (elect_one()) {
      const int rt = ((bid >> 1) & 7) * 2 + (bid & 1);
#pragma unroll
      for (int i = 0; i < 6; i++) mbar_init(sb + B_FULL + 8 * i, 1);
#pragma unroll
      for (int it = 0; it < 6; it++) {
        const int s = (it + 2) % 6;
        const uint32_t st = sb + (s >> 1) * G_PB, fb = sb + B_FULL + 8 * s;
        mbar_expect_tx(fb, (it & 1) ? G_WB : G_XB + G_WB);
        if (!(it & 1)) tma2d(st, &P.tmX, it * 32, rt * 128, fb);
      }
#pragma unroll
      for (int i = 0; i < 6; i++) mbar_init(sb + B_EMPTY + 8 * i, 4);
      mbar_init(sb + B_BD, 1); mbar_init(sb + B_QR, 8);
    }
  }
  __syncthreads();
  asm volatile("barrier.cluster.arrive.release.aligned;" ::: "memory");
  if (wg == 4) {
    asm volatile("setmaxnreg.dec.sync.aligned.u32 32;");
    if (wp == 0) agent_g(P, sb);
    else asm volatile("barrier.cluster.wait.aligned;" ::: "memory");
    bar_sync(11, 128);
    asm volatile("setmaxnreg.inc.sync.aligned.u32 64;");
    branch_a(sm, sb);
    if (wp == 0) agent_t(sb);
    return;
  }
  asm volatile("barrier.cluster.wait.aligned;" ::: "memory");
  {
    const int pr = bid >> 1, rt = (pr & 7) * 2 + (bid & 1), ct = pr >> 3;
    const int h = bid >> 2, part = bid & 3, odd = h & 1;
    const uint32_t stg = sb + SM_STG;
    if (wg < 2) {
      asm volatile("setmaxnreg.inc.sync.aligned.u32 168;");
      float acc[120];
      int s = 2, ph = 0;
#pragma unroll 1
      for (int round = 0; round < 2; round++) {
        int prev = 0;
#pragma unroll 1
        for (int kb = 0; kb < 20; kb++) {
          mbar_wait(sb + B_FULL + 8 * s, ph);
          const uint32_t xa = (sl + (s >> 1) * G_PB + wg * 8192 + (s & 1) * 64) >> 4, wa = (sl + (s >> 1) * G_PB + G_XB + (s & 1) * G_WB) >> 4;
          wg_fence();
#pragma unroll
          for (int k = 0; k < 2; k++) {
            mma_n128(acc, mkdesc(xa + 2 * k, 16, 1024, 1), mkdesc(wa + 128 * k, 4096, 1024, 1), (kb | k) != 0);
            mma_n112(acc + 64, mkdesc(xa + 2 * k, 16, 1024, 1), mkdesc(wa + 512 + 128 * k, 4096, 1024, 1), (kb | k) != 0);
          }
          wg_commit();
          if (kb > 0) {
            wg_wait<1>();
            if ((tid & 127) < 2) mbar_arrive_cluster(sb + B_EMPTY + 8 * prev, tid & 1);
          }
          prev = s;
          if (s == 1) ph ^= 1;
          if (++s == 6) s = 0;
        }
        wg_wait<0>();
        fence_f<120>(acc);
        if ((tid & 127) < 2) mbar_arrive_cluster(sb + B_EMPTY + 8 * prev, tid & 1);
        if (round == 0) {
          g_epilogue<true>(acc, stg, ct, wg, wp, lane);
          fence_async();
          bar_arrive(1, 416);
        } else {
          bar_sync(2, 416);
          g_epilogue<false>(acc, stg, ct, wg, wp, lane);
          fence_async();
          bar_arrive(9, 288);
        }
      }
      asm volatile("setmaxnreg.dec.sync.aligned.u32 104;");
    } else {
      asm volatile("setmaxnreg.dec.sync.aligned.u32 56;");
      const int i8 = tid - 256;
      {
        uint4 v[4];
        uint32_t off[4];
#pragma unroll
        for (int u = 0; u < 4; u++) {
          const uint32_t c = bid * 100 + min((i8 >> 3) + 32 * u, 99), grp = c / 80, pc = c - grp * 80, k = grp * 8 + (i8 & 7), cb = pc / 10;
          v[u] = __ldg((const uint4*)(k < 640 ? P.woA + k * 640 : P.woB + (k - 640) * 640) + pc);
          off[u] = cb * (204800 - 1280) + pc * 128 + grp * 1280 + (i8 & 7) * 16;
        }
        if (wg == 2 && wp < 3) {
          const int kc = i8 / 24, f = i8 - kc * 24, d0 = kc == 3 ? (odd ? -4 : 16) : kc * 8 + odd * 4;
          const uint16_t* wsrc = (const uint16_t*)P.w_phi + h * 400 + d0 * 20 + (f < 20 ? f : f - 4);
          const bool lo = kc < 2 || (kc == 3 && !odd), hi = kc < 2 || (kc == 3 && odd);
          uint32_t w[8];
#pragma unroll
          for (int e = 0; e < 8; e++) w[e] = (e < 4 ? lo : hi) ? __ldg(wsrc + e * 20) : 0u;
          *(uint4*)(sm + SM_WPHI + i8 * 16) = make_uint4(w[0] | w[1] << 16, w[2] | w[3] << 16, w[4] | w[5] << 16, w[6] | w[7] << 16);
        } else if (wg == 2) {
          ((uint32_t*)(sm + SM_FLAG))[i8 - 96] = 0;
          if (elect_one()) {
#pragma unroll
            for (int i = 0; i < 32; i++) mbar_init(sb + B_KV + 8 * i, 1);
#pragma unroll
            for (int i = 16; i < 26; i++) mbar_arrive(sb + B_KV + 8 * i);
            mbar_init(sb + B_AV, 1); mbar_init(sb + B_AQ, 1); mbar_init(sb + B_KD, 4); mbar_init(sb + B_QD, 16);
#pragma unroll
            for (int i = 0; i < 16; i++) mbar_init(sb + B_P + 16 * i, 16);
#pragma unroll
            for (int i = 0; i < 8; i++) { mbar_init(sb + B_OF + 8 * i, 1); mbar_init(sb + B_OE + 8 * i, 4); }
            asm volatile("fence.mbarrier_init.release.cluster;" ::: "memory");
          }
        } else {
          const int t7 = i8 - 128;
          ((uint2*)(sm + SM_ZERO))[t7] = make_uint2(0u, 0u);
          if (t7 < 80) {
            const int fc = t7 >> 4, n = (t7 >> 1) & 7, neg = (t7 & 1) ? fc > 1 : fc > 2;
            const uint32_t w = n == neg ? 0x3F803F80u : 0u;
            ((uint2*)(sm + SM_IND))[t7] = make_uint2(w, w);
          }
        }
        if (part == 0 && i8 < 240) ((float4*)g_kvs)[h * 240 + i8] = make_float4(0.f, 0.f, 0.f, 0.f);
        fence_async();
#pragma unroll
        for (int u = 0; u < 4; u++) *(uint4*)(g_wo + off[u]) = v[u];
      }
      {
        const int row = bid * 16 + (i8 >> 5) * 2;
        float z0 = 0.f, z1 = 0.f;
#pragma unroll
        for (int i = 0; i < 3; i++) {
          if (lane + 32 * i < 80) {
            const uint4 gw = __ldg((const uint4*)P.gate_w + lane + 32 * i);
            const uint4 a = __ldg((const uint4*)(P.x + row * D_) + lane + 32 * i), b = __ldg((const uint4*)(P.x + (row + 1) * D_) + lane + 32 * i);
            const uint32_t gv[4] = {gw.x, gw.y, gw.z, gw.w}, av[4] = {a.x, a.y, a.z, a.w}, bv[4] = {b.x, b.y, b.z, b.w};
#pragma unroll
            for (int e = 0; e < 4; e++) {
              const float gl = bf_lo(gv[e]), gh = bf_hi(gv[e]);
              z0 = fmaf(bf_lo(av[e]), gl, fmaf(bf_hi(av[e]), gh, z0));
              z1 = fmaf(bf_lo(bv[e]), gl, fmaf(bf_hi(bv[e]), gh, z1));
            }
          }
        }
        float z = (lane & 1) ? z1 : z0;
        z += __shfl_xor_sync(~0u, (lane & 1) ? z0 : z1, 1);
#pragma unroll
        for (int o = 16; o > 1; o >>= 1) z += __shfl_xor_sync(~0u, z, o);
        if (lane < 2) g_gate[row + lane] = __fdividef(1.f, 1.f + __expf(-z));
      }
      if (wg == 3) {
        const int t7 = tid & 127;
        bar_sync(1, 416);
        const bool pl = (PMASK >> (t7 >> 3)) & 1;
#pragma unroll 2
        for (int q = 0; q < 12; q++) {
          const int sidx = ct * 12 + q, type = sidx >> 5;
          if (type == 0) continue;
          const uint32_t ad = stg + q * SLICE + (type == 1 ? t7 * 16 : (t7 >> 3) * 384 + (t7 & 7) * 16), cs = type == 1 ? 2048 : 128;
          const uint4 c0 = lds128(ad), c1 = lds128(ad + cs), c2 = lds128(ad + 2 * cs);
          const uint32_t v[10] = {c0.x, c0.y, c0.z, c0.w, c1.x, c1.y, c1.z, c1.w, (q & 1) ? c2.z : c2.x, (q & 1) ? c2.w : c2.y};
          float r;
          if (type == 1) {
            float r1 = 0.f;
            r = 0.f;
#pragma unroll
            for (int i = 0; i < 10; i++) { const float2 f = __half22float2(*(const __half2*)&v[i]); r = fmaf(f.x, f.x, r); r1 = fmaf(f.y, f.y, r1); }
            r += r1;
            if (pl) r *= 262144.f;
          } else {
            uint32_t m = 0;
#pragma unroll
            for (int i = 0; i < 10; i++) m = __vmaxu2(m, v[i] & 0x7fff7fffu);
            m = max(m & 0xffffu, m >> 16);
            r = __half2float(__ushort_as_half((unsigned short)m));
          }
          const uint32_t u = __reduce_max_sync(~0u, __float_as_uint(r));
          if (lane == 0) ((uint32_t*)(sm + SM_RED))[q * 4 + wp] = u;
        }
        bar_arrive(2, 416);
        bar_sync(7, 128);
        if (t7 < 12) {
          const int sidx = ct * 12 + t7, type = sidx >> 5, head = sidx & 31;
          const uint4 u = *(const uint4*)(sm + SM_RED + t7 * 16);
          if (type != 0) g_stat[head * 32 + (type - 1) * 16 + rt] = __uint_as_float(max(max(u.x, u.y), max(u.z, u.w)));
        }
        fence_async();
        bar_arrive(3, 256);
      } else if (wp == 1) {
        bar_sync(1, 416);
        if (lane == 0) {
#pragma unroll 1
          for (int q = 0; q < 12; q++) {
            const int sidx = ct * 12 + q, type = sidx >> 5, head = sidx & 31;
            bulk_s2g(type == 0 ? g_qB + ((size_t)head * 16 + rt) * SLICE : g_kvB + ((size_t)head * 16 + rt) * KVB + (type - 1) * SLICE, stg + q * SLICE, SLICE);
            bulk_commit();
            asm volatile("cp.async.bulk.wait_group 1;" ::: "memory");
          }
          bulk_wait_all();
        }
        __syncwarp();
        bar_arrive(2, 416);
        bar_sync(3, 256);
        if (lane == 0) signal(C_B);
        __syncwarp();
      } else {
        bar_arrive(3, 256);
      }
      mbar_wait(sb + B_BD, 0);
      prep_q(sm, sb, tid - 256, odd);
      fence_async();
      __syncwarp();
      if (lane == 0) mbar_arrive(sb + B_QR);
      asm volatile("setmaxnreg.inc.sync.aligned.u32 104;");
    }
  }
  uint32_t oh[6], s[32], p[32];
  float o[12];
  mbar_wait(sb + B_QR, 0);
  const uint32_t zero = *(volatile uint32_t*)(sm + SM_ZERO);
#pragma unroll
  for (int i = 0; i < 12; i++) o[i] = 0.f;
  const uint32_t stops = 0x8480u;
#pragma unroll 1
  for (int j0 = 0; j0 < 16;) {
    const int jj = j0 + __ffs(stops >> j0) - 1;
    uint32_t bar = sb + B_KV + 16 * j0;
    const uint32_t k16 = (sl + KV0 + (j0 < 8 ? 2 * j0 : 31 - 2 * j0) * KVB) >> 4;
    const uint32_t qoff = SM_Q + wg * SLICE + (j0 >> 3) * 1024;
    const uint64_t dq0 = mkdesc((sl + qoff) >> 4, 2048, 128, 0), dq1 = mkdesc((sl + qoff + 4096) >> 4, SM_ZERO - 4096 - qoff, 128, 0);
    uint64_t dk0 = mkdesc(k16, 2048, 128, 0), dk1 = mkdesc(k16 + 256, 2048, 128, 0), dv[8];
#pragma unroll
    for (int i = 0; i < 8; i++) dv[i] = mkdesc(k16 + ((SLICE + i * 768) >> 4), 384, 128, 0);
#pragma unroll
    for (int i = 0; i < 6; i++) oh[i] = 0;
    fence_u<6>(oh);
    const uint32_t inc = j0 < 8 ? (KVB >> 4) : -(KVB >> 4);
#pragma unroll 1
    for (; j0 <= jj; j0++)
#pragma unroll
      for (int u = 0; u < 2; u++) {
        mbar_wait_u(bar, 0); bar += 8;
        wg_fence();
        mma_qk_first(s, dq0, dk0); mma_qk_acc(s, dq1, dk1);
        wg_commit();
        dk0 = addlo_r(dk0, inc); dk1 = addlo_r(dk1, inc);
        wg_wait<0>();
        fence_u<32>(s);
        if (u == 0 && elect_one()) mbar_arrive(bar + (B_P - B_KV - 8));
#pragma unroll
        for (int hf = 0; hf < 2; hf++) {
#pragma unroll
          for (int i = hf * 8; i < hf * 8 + 8; i++) {
            if ((PMASK >> i) & 1) { p[2 * i] = exp_poly(s[2 * i], zero); p[2 * i + 1] = exp_poly(s[2 * i + 1], zero); }
            else { p[2 * i] = exp_mufu(s[2 * i]); p[2 * i + 1] = exp_mufu(s[2 * i + 1]); }
          }
          wg_fence();
#pragma unroll
          for (int i = hf * 4; i < hf * 4 + 4; i++) mma_pv(oh, p + 4 * i, dv[i]);
        }
        wg_commit();
#pragma unroll
        for (int i = 0; i < 8; i++) dv[i] = addlo_r(dv[i], inc);
      }
    wg_wait<0>();
    fence_u<6>(oh);
#pragma unroll
    for (int i = 0; i < 6; i++) { const float2 v = __half22float2(*(__half2*)&oh[i]); o[2 * i] += v.x; o[2 * i + 1] += v.y; }
    const int tid = fresh_tid(), bid = fresh_bid(), lane = tid & 31, g = lane >> 2, t = lane & 3;
    const int wg = __shfl_sync(~0u, tid >> 7, 0), wp = __shfl_sync(~0u, (tid >> 5) & 3, 0);
    const int h = bid >> 2, part = bid & 3, odd = h & 1, rloc = wg * 128 + wp * 16 + g;
    const float* gate = (const float*)(sm + SM_GATE) + rloc;
    const int src = (lane & ~3) | (odd ? 0 : 2);
    if ((jj & 7) == 7) {
      const float l0 = __shfl_sync(~0u, o[8], src), l1 = __shfl_sync(~0u, o[10], src);
      float chk = 0.f;
#pragma unroll
      for (int i = 0; i < 12; i++) chk += fabsf(o[i]);
      volatile uint32_t* flag = (volatile uint32_t*)(sm + SM_FLAG) + wg * 8 + (jj >> 3) * 4 + wp;
      const bool ok = *flag == 0 && l0 >= 32.f && l1 >= 32.f && chk < 1e30f;
      if (!__all_sync(~0u, ok)) { if (lane == 0) *flag = 1; }
      else {
        const float r0 = __fdividef(1.f - gate[(jj >> 3) * 64], l0), r1 = __fdividef(1.f - gate[(jj >> 3) * 64 + 8], l1);
        uint32_t v[6];
#pragma unroll
        for (int c = 0; c < 3; c++) { v[2 * c] = pack_b(o[4 * c] * r0, o[4 * c + 1] * r0); v[2 * c + 1] = pack_b(o[4 * c + 2] * r1, o[4 * c + 3] * r1); }
        store_o(v, 80, h, part * 512 + rloc + (jj >> 3) * 64, t);
      }
#pragma unroll
      for (int i = 0; i < 12; i++) o[i] = 0.f;
    } else {
      mbar_wait(sb + B_AQ, 0);
      const uint32_t kvi = (sl + SM_KVI) >> 4, img = (sl + SM_AQ + wg * SLICE) >> 4;
      mbar_wait(sb + B_KD, 0);
#pragma unroll 1
      for (int tl = 0; tl < 2; tl++) {
        float n[24];
        uint32_t e[12], v[6];
        float d[12];
        wg_fence();
        phi_logits(d, img + 64 * tl, (sl + SM_WPHI) >> 4);
        wg_commit();
        wg_wait<0>();
        phi_exp(e, d, t, zero);
        wg_fence();
        mma_b48_rs0(n, e, mkdesc(kvi, 768, 128, 0));
        mma_b48_rs(n, e + 4, mkdesc(kvi + 96, 768, 128, 0));
        mma_b48_rs(n, e + 8, mkdesc(kvi + 144, 768, 128, 0));
        wg_commit();
        wg_wait<0>();
        phi_out(v, n, gate + tl * 64, src);
        store_o(v, 0, h, part * 512 + rloc + tl * 64, t);
      }
      __syncwarp();
      if (lane == 0) mbar_arrive(sb + B_QD);
    }
    __syncwarp();
  }
  {
    const int tid = fresh_tid(), bid = fresh_bid(), lane = tid & 31;
    const int wg = __shfl_sync(~0u, tid >> 7, 0), wp = __shfl_sync(~0u, (tid >> 5) & 3, 0);
    if (wg >= 2) {
      bar_sync(8, 512);
      if (wg == 2 && tid < 264) mbar_arrive_cluster(sb + B_OE + 48 + (tid & 2) * 4, tid & 1);
      if (__any_sync(~0u, ((const uint32_t*)(sm + SM_FLAG))[lane] != 0)) attn_fallback((const uint32_t*)(sm + SM_FLAG), bid >> 2, bid & 3, P.x, P.wB);
      if (tid == 384) signal(C_OB + bid * 8);
    } else {
      bar_arrive(8, 512);
    }
    if (wg < 2) {
      float acc[40];
#pragma unroll 1
      for (int it = 0; it < 20; it++) {
        const int s = it & 7;
        bool rel = it > 0 && it <= 12;
        if (!mbar_test_wg(sb + B_OF + 8 * s, (it >> 3) & 1, 4 + wg)) {
          wg_wait<0>();
          if (rel && (tid & 127) < 2) mbar_arrive_cluster(sb + B_OE + 8 * ((it - 1) & 7), tid & 1);
          rel = false;
          mbar_wait(sb + B_OF + 8 * s, (it >> 3) & 1);
        }
        const uint32_t aa = (sl + o_slot(s) + wg * 1024) >> 4, wa = (sl + o_slot(s) + O_AB) >> 4;
        wg_fence();
#pragma unroll
        for (int k = 0; k < 4; k++) mma_n80(acc, mkdesc(aa + 256 * k, 2048, 128, 0), mkdesc(wa + 160 * k, 1280, 128, 0), (it | k) != 0);
        wg_commit();
        wg_wait<1>();
        if (rel && (tid & 127) < 2) mbar_arrive_cluster(sb + B_OE + 8 * ((it - 1) & 7), tid & 1);
      }
      wg_wait<0>();
      fence_f<40>(acc);
      const uint32_t stg = sb + o_slot(6) + wg * 10240;
      const uint32_t ad = stg + (wp * 16 + ((lane >> 3) & 1) * 8 + (lane & 7)) * 160 + (lane >> 4) * 16;
      bar_sync(1, 256);
#pragma unroll
      for (int i = 0; i < 5; i++)
        stsm4(ad + i * 32, pack_b(acc[8 * i], acc[8 * i + 1]), pack_b(acc[8 * i + 2], acc[8 * i + 3]), pack_b(acc[8 * i + 4], acc[8 * i + 5]), pack_b(acc[8 * i + 6], acc[8 * i + 7]));
      fence_async();
      bar_sync(4 + wg, 128);
      if ((tid & 127) == 0) {
        tma2d_store(&P.tmOut, stg, (bid & 7) * 80, (bid >> 3) * 128 + wg * 64);
        bulk_commit();
        asm volatile("cp.async.bulk.wait_group.read 0;" ::: "memory");
      }
    }
  }
}

typedef CUresult (*EncodeFn)(CUtensorMap*, CUtensorMapDataType, cuuint32_t, void*, const cuuint64_t*, const cuuint64_t*, const cuuint32_t*,
                             const cuuint32_t*, CUtensorMapInterleave, CUtensorMapSwizzle, CUtensorMapL2promotion, CUtensorMapFloatOOBfill);

void encode(EncodeFn fn, CUtensorMap* m, const void* p, int rank, const cuuint64_t* dims, const cuuint64_t* strides, const cuuint32_t* box, CUtensorMapSwizzle swz) {
  const cuuint32_t es[3] = {1, 1, 1};
  CUresult r = fn(m, CU_TENSOR_MAP_DATA_TYPE_BFLOAT16, rank, const_cast<void*>(p), dims, strides, box, es, CU_TENSOR_MAP_INTERLEAVE_NONE, swz,
                  CU_TENSOR_MAP_L2_PROMOTION_L2_256B, CU_TENSOR_MAP_FLOAT_OOB_FILL_NONE);
  if (r != CUDA_SUCCESS) fprintf(stderr, "tensor map encode failed: %d\n", (int)r);
}

}

extern "C" void kernel_launch(void* const* d_in, const int* in_sizes, int n_in, void* d_out, int out_size) {
  (void)in_sizes; (void)n_in; (void)out_size;
  static EncodeFn fn = nullptr;
  if (!fn) {
    void* p = nullptr;
    cudaDriverEntryPointQueryResult qr;
    cudaGetDriverEntryPoint("cuTensorMapEncodeTiled", &p, cudaEnableDefault, &qr);
    fn = (EncodeFn)p;
    cudaFuncSetAttribute(fused_kernel, cudaFuncAttributeMaxDynamicSharedMemorySize, SM_TOTAL);
  }
  Params P;
  P.x = (const __nv_bfloat16*)d_in[0];
  P.w_phi = (const __nv_bfloat16*)d_in[2];
  P.wB = (const __nv_bfloat16*)d_in[5];
  P.gate_w = (const __nv_bfloat16*)d_in[7];
  P.woA = (const __nv_bfloat16*)d_in[3];
  P.woB = (const __nv_bfloat16*)d_in[6];
  {
    const cuuint64_t d[2] = {640, 2048}, st[1] = {1280};
    const cuuint32_t box[2] = {64, 128}, obox[2] = {80, 64};
    encode(fn, &P.tmX, d_in[0], 2, d, st, box, CU_TENSOR_MAP_SWIZZLE_128B);
    encode(fn, &P.tmOut, d_out, 2, d, st, obox, CU_TENSOR_MAP_SWIZZLE_NONE);
  }
  {
    const cuuint64_t d[2] = {1920, 640}, st[1] = {3840};
    const cuuint32_t box[2] = {64, 32};
    encode(fn, &P.tmWA, d_in[1], 2, d, st, box, CU_TENSOR_MAP_SWIZZLE_128B);
    encode(fn, &P.tmWB, d_in[5], 2, d, st, box, CU_TENSOR_MAP_SWIZZLE_128B);
  }
  fused_kernel<<<128, 640, SM_TOTAL, cudaStreamPerThread>>>(P);
}
```

```cpp
#include <cuda_runtime.h>
#include <cuda_bf16.h>
#include <cuda_fp16.h>
#include <cuda.h>
#include <stdint.h>
#include <stdio.h>


namespace {

constexpr int S_ = 2048, D_ = 640, H_ = 32;
constexpr int SLICE = 6144;
constexpr int KVB = 2 * SLICE;
constexpr uint32_t PMASK = 0xADADu;
constexpr float QSCALE = 0.32259642f;

__device__ __align__(1024) uint8_t g_qB[H_ * 16 * SLICE];
__device__ __align__(1024) uint8_t g_kvB[H_ * 16 * KVB];
__device__ __align__(1024) uint8_t g_A[3 * H_ * 16 * SLICE];
__device__ __align__(1024) uint8_t g_o[16 * 160 * 2048];
__device__ __align__(1024) uint8_t g_wo[8 * 20 * 10240];
__device__ __align__(128) float g_stat[H_ * 32];
__device__ __align__(16) float g_gate[S_];
__device__ __align__(16) float g_kvs[H_ * 40 * 24];
__device__ __align__(16) __nv_bfloat16 g_fb[H_ * S_ * 40];
constexpr int C_B = 0, C_EXIT = 64, C_OA = 96, C_KV = 224, C_A = C_KV + 32 * 32, C_OB = C_A + 4, C_N = C_A + 128 * 8;
__device__ __align__(128) unsigned int g_cnt[C_N];

__device__ __forceinline__ uint32_t smem_u32(const void* p) { return (uint32_t)__cvta_generic_to_shared(p); }
__device__ __forceinline__ uint64_t mkdesc(uint32_t a16, uint32_t lbo, uint32_t sbo, uint32_t swz) {
  uint32_t lo = a16 + ((lbo >> 4) << 16);
  uint32_t hi = (sbo >> 4) | (swz << 30);
  return ((uint64_t)hi << 32) | lo;
}
__device__ __forceinline__ uint64_t addlo_r(uint64_t d, uint32_t inc) {
  asm volatile("{.reg .b32 lo, hi; mov.b64 {lo,hi}, %0; add.u32 lo, lo, %1; mov.b64 %0, {lo,hi};}" : "+l"(d) : "r"(inc));
  return d;
}
__device__ __forceinline__ void wg_fence() { asm volatile("wgmma.fence.sync.aligned;" ::: "memory"); }
__device__ __forceinline__ void wg_commit() { asm volatile("wgmma.commit_group.sync.aligned;" ::: "memory"); }
template <int N> __device__ __forceinline__ void wg_wait() { asm volatile("wgmma.wait_group.sync.aligned %0;" ::"n"(N) : "memory"); }
template <int N> __device__ __forceinline__ void fence_f(float* r) {
#pragma unroll
  for (int i = 0; i < N; i++) asm volatile("" : "+f"(r[i])::"memory");
}
template <int N> __device__ __forceinline__ void fence_u(uint32_t* r) {
#pragma unroll
  for (int i = 0; i < N; i++) asm volatile("" : "+r"(r[i])::"memory");
}
__device__ __forceinline__ void mbar_init(uint32_t bar, uint32_t cnt) { asm volatile("mbarrier.init.shared::cta.b64 [%0], %1;" ::"r"(bar), "r"(cnt) : "memory"); }
__device__ __forceinline__ void mbar_expect_tx(uint32_t bar, uint32_t bytes) { asm volatile("mbarrier.arrive.expect_tx.shared::cta.b64 _, [%0], %1;" ::"r"(bar), "r"(bytes) : "memory"); }
__device__ __forceinline__ void mbar_wait(uint32_t bar, uint32_t parity) {
  asm volatile(
      "{\n.reg .pred p;\n.reg .u32 n;\nmov.u32 n, 0;\n"
      "W: mbarrier.try_wait.parity.shared::cta.b64 p, [%0], %1;\n@p bra D;\n"
      "add.u32 n, n, 1;\nsetp.lt.u32 p, n, 0x1000000;\n@p bra W;\ntrap;\nD:\n}" ::"r"(bar), "r"(parity) : "memory");
}
__device__ __forceinline__ bool mbar_test_wg(uint32_t bar, uint32_t parity, int id) {
  uint32_t r;
  asm volatile("{.reg .pred p, q; mbarrier.test_wait.parity.shared::cta.b64 p, [%1], %2; bar.red.and.pred q, %3, 128, p; selp.u32 %0, 1, 0, q;}"
               : "=r"(r) : "r"(bar), "r"(parity), "r"(id) : "memory");
  return r != 0;
}
__device__ __forceinline__ void mbar_wait_z(uint32_t bar, uint32_t parity) {
  asm volatile(
      "{\n.reg .pred p;\n.reg .u32 n;\nmov.u32 n, 0;\n"
      "W: mbarrier.try_wait.parity.shared::cta.b64 p, [%0], %1, 20000;\n@p bra D;\n"
      "add.u32 n, n, 1;\nsetp.lt.u32 p, n, 0x100000;\n@p bra W;\ntrap;\nD:\n}" ::"r"(bar), "r"(parity) : "memory");
}
__device__ __forceinline__ void mbar_wait_u(uint32_t bar, uint32_t parity) {
  asm volatile("{\n.reg .pred p;\nW: mbarrier.try_wait.parity.shared::cta.b64 p, [%0], %1;\n@p bra D;\nbra W;\nD:\n}" ::"r"(bar), "r"(parity) : "memory");
}
__device__ __forceinline__ void mbar_arrive_cluster(uint32_t bar, uint32_t cta) {
  asm volatile("{.reg .b32 r; mapa.shared::cluster.u32 r, %0, %1; mbarrier.arrive.shared::cluster.b64 _, [r];}" ::"r"(bar), "r"(cta) : "memory");
}
__device__ __forceinline__ void bulk_g2s(uint32_t dst, const void* src, uint32_t bytes, uint32_t bar) {
  asm volatile("cp.async.bulk.shared::cluster.global.mbarrier::complete_tx::bytes [%0], [%1], %2, [%3];" ::"r"(dst), "l"(src), "r"(bytes), "r"(bar) : "memory");
}
__device__ __forceinline__ void bulk_g2s_mc(uint32_t dst, const void* src, uint32_t bytes, uint32_t bar, uint16_t mask) {
  asm volatile("cp.async.bulk.shared::cluster.global.mbarrier::complete_tx::bytes.multicast::cluster [%0], [%1], %2, [%3], %4;" ::"r"(dst), "l"(src), "r"(bytes), "r"(bar), "h"(mask) : "memory");
}
__device__ __forceinline__ void bulk_s2g(void* dst, uint32_t src, uint32_t bytes) {
  asm volatile("cp.async.bulk.global.shared::cta.bulk_group [%0], [%1], %2;" ::"l"(dst), "r"(src), "r"(bytes) : "memory");
}
__device__ __forceinline__ void tma2d(uint32_t dst, const CUtensorMap* m, int c0, int c1, uint32_t bar) {
  asm volatile("cp.async.bulk.tensor.2d.shared::cluster.global.mbarrier::complete_tx::bytes [%0], [%1, {%3, %4}], [%2];" ::"r"(dst), "l"(m), "r"(bar), "r"(c0), "r"(c1) : "memory");
}
__device__ __forceinline__ void tma2d_mc(uint32_t dst, const CUtensorMap* m, int c0, int c1, uint32_t bar, uint16_t mask) {
  asm volatile("cp.async.bulk.tensor.2d.shared::cluster.global.mbarrier::complete_tx::bytes.multicast::cluster [%0], [%1, {%3, %4}], [%2], %5;" ::"r"(dst), "l"(m), "r"(bar), "r"(c0), "r"(c1), "h"(mask) : "memory");
}
__device__ __forceinline__ void tma2d_store(const CUtensorMap* m, uint32_t src, int c0, int c1) {
  asm volatile("cp.async.bulk.tensor.2d.global.shared::cta.bulk_group [%0, {%2, %3}], [%1];" ::"l"(m), "r"(src), "r"(c0), "r"(c1) : "memory");
}
__device__ __forceinline__ void bulk_commit() { asm volatile("cp.async.bulk.commit_group;" ::: "memory"); }
__device__ __forceinline__ void bulk_wait_all() { asm volatile("cp.async.bulk.wait_group 0;" ::: "memory"); }
__device__ __forceinline__ void fence_async() { asm volatile("fence.proxy.async.shared::cta;" ::: "memory"); }
__device__ __forceinline__ void bar_sync(int id, int n) { asm volatile("bar.sync %0, %1;" ::"r"(id), "r"(n) : "memory"); }
__device__ __forceinline__ void bar_arrive(int id, int n) { asm volatile("bar.arrive %0, %1;" ::"r"(id), "r"(n) : "memory"); }
__device__ __forceinline__ void mbar_arrive(uint32_t bar) { asm volatile("mbarrier.arrive.shared::cta.b64 _, [%0];" ::"r"(bar) : "memory"); }
__device__ __forceinline__ void fence_gpu() { asm volatile("fence.acq_rel.gpu;" ::: "memory"); }
__device__ __forceinline__ void fence_async_g() { asm volatile("fence.proxy.async.global;" ::: "memory"); }
__device__ __forceinline__ void signal(int c) { fence_gpu(); asm volatile("red.relaxed.gpu.global.add.u32 [%0], 1;" ::"l"(g_cnt + c) : "memory"); }
__device__ __forceinline__ void await(int c, uint32_t target) {
  asm volatile(
      "{\n.reg .pred p;\n.reg .u32 n, v;\nmov.u32 n, 0;\n"
      "W: ld.acquire.gpu.global.u32 v, [%0];\nsetp.ge.u32 p, v, %1;\n@p bra D;\n"
      "nanosleep.u32 64;\nadd.u32 n, n, 1;\nsetp.lt.u32 p, n, 0x400000;\n@p bra W;\ntrap;\nD:\n}" ::"l"(g_cnt + c), "r"(target) : "memory");
}
__device__ __forceinline__ void await_all(int c, uint32_t target) {
  asm volatile(
      "{\n.reg .pred p;\n.reg .u32 n, v;\nmov.u32 n, 0;\n"
      "W: ld.acquire.gpu.global.u32 v, [%0];\nsetp.ge.u32 p, v, %1;\nvote.sync.all.pred p, p, 0xffffffff;\n@p bra.uni D;\n"
      "nanosleep.u32 64;\nadd.u32 n, n, 1;\nsetp.lt.u32 p, n, 0x400000;\n@p bra.uni W;\ntrap;\nD:\n}" ::"l"(g_cnt + c), "r"(target) : "memory");
}
__device__ __forceinline__ uint32_t await_mask(int c, uint32_t need) {
  uint32_t m;
  asm volatile(
      "{\n.reg .pred p;\n.reg .u32 n, v;\nmov.u32 n, 0;\n"
      "W: ld.acquire.gpu.global.u32 v, [%1];\nsetp.ne.u32 p, v, 0;\nvote.sync.ballot.b32 %0, p, 0xffffffff;\n"
      "and.b32 v, %0, %2;\nsetp.eq.u32 p, v, %2;\n@p bra.uni D;\n"
      "add.u32 n, n, 1;\nsetp.lt.u32 p, n, 0x400000;\n@p bra.uni W;\ntrap;\nD:\n}" : "=r"(m) : "l"(g_cnt + c), "r"(need) : "memory");
  return m;
}
__device__ __forceinline__ bool elect_one() {
  uint32_t p;
  asm volatile("{.reg .pred p; elect.sync _|p, 0xffffffff; selp.u32 %0, 1, 0, p;}" : "=r"(p));
  return p != 0;
}
__device__ __forceinline__ int fresh_tid() { int v; asm volatile("mov.u32 %0, %%tid.x;" : "=r"(v)); return v < 128 ? v + 512 : v - 128; }
__device__ __forceinline__ int fresh_bid() { int v; asm volatile("mov.u32 %0, %%ctaid.x;" : "=r"(v)); return v; }
__device__ __forceinline__ void stsm2(uint32_t addr, uint32_t a, uint32_t b) {
  asm volatile("stmatrix.sync.aligned.m8n8.x2.shared.b16 [%0], {%1,%2};" ::"r"(addr), "r"(a), "r"(b) : "memory");
}
__device__ __forceinline__ uint4 lds128(uint32_t a) { uint4 v; asm volatile("ld.shared.v4.u32 {%0,%1,%2,%3}, [%4];" : "=r"(v.x), "=r"(v.y), "=r"(v.z), "=r"(v.w) : "r"(a) : "memory"); return v; }
__device__ __forceinline__ void stsm4(uint32_t addr, uint32_t a, uint32_t b, uint32_t c, uint32_t d) {
  asm volatile("stmatrix.sync.aligned.m8n8.x4.shared.b16 [%0], {%1,%2,%3,%4};" ::"r"(addr), "r"(a), "r"(b), "r"(c), "r"(d) : "memory");
}
__device__ __forceinline__ uint32_t pack_h(float lo, float hi) { uint32_t r; asm("cvt.rn.f16x2.f32 %0, %1, %2;" : "=r"(r) : "f"(hi), "f"(lo)); return r; }
__device__ __forceinline__ uint32_t pack_b(float lo, float hi) { uint32_t r; asm("cvt.rn.bf16x2.f32 %0, %1, %2;" : "=r"(r) : "f"(hi), "f"(lo)); return r; }
__device__ __forceinline__ float ex2f(float x) { float r; asm("ex2.approx.ftz.f32 %0, %1;" : "=f"(r) : "f"(x)); return r; }
__device__ __forceinline__ float bf_lo(uint32_t u) { return __uint_as_float(u << 16); }
__device__ __forceinline__ float bf_hi(uint32_t u) { return __uint_as_float(u & 0xffff0000u); }

#define F4(o) "+f"(d[o + 0]), "+f"(d[o + 1]), "+f"(d[o + 2]), "+f"(d[o + 3])
#define F8(o) F4(o), F4(o + 4)
#define F40(o) F8(o), F8(o + 8), F8(o + 16), F8(o + 24), F8(o + 32)
#define RU8(o) "+r"(d[o + 0]), "+r"(d[o + 1]), "+r"(d[o + 2]), "+r"(d[o + 3]), "+r"(d[o + 4]), "+r"(d[o + 5]), "+r"(d[o + 6]), "+r"(d[o + 7])
#define WU8(o) "=r"(d[o + 0]), "=r"(d[o + 1]), "=r"(d[o + 2]), "=r"(d[o + 3]), "=r"(d[o + 4]), "=r"(d[o + 5]), "=r"(d[o + 6]), "=r"(d[o + 7])
#define A4 "r"(a[0]), "r"(a[1]), "r"(a[2]), "r"(a[3])

__device__ __forceinline__ void mma_n128(float* d, uint64_t a, uint64_t b, int acc) {
  asm volatile(
      "{.reg .pred p; setp.ne.b32 p, %66, 0;\n"
      "wgmma.mma_async.sync.aligned.m64n128k16.f32.bf16.bf16 {"
      "%0,%1,%2,%3,%4,%5,%6,%7,%8,%9,%10,%11,%12,%13,%14,%15,%16,%17,%18,%19,%20,%21,%22,%23,"
      "%24,%25,%26,%27,%28,%29,%30,%31,%32,%33,%34,%35,%36,%37,%38,%39,%40,%41,%42,%43,%44,%45,%46,%47,"
      "%48,%49,%50,%51,%52,%53,%54,%55,%56,%57,%58,%59,%60,%61,%62,%63"
      "}, %64, %65, p, 1, 1, 0, 1;}"
      : F40(0), F8(40), F8(48), F8(56)
      : "l"(a), "l"(b), "r"(acc));
}
__device__ __forceinline__ void mma_n112(float* d, uint64_t a, uint64_t b, int acc) {
  asm volatile(
      "{.reg .pred p; setp.ne.b32 p, %58, 0;\n"
      "wgmma.mma_async.sync.aligned.m64n112k16.f32.bf16.bf16 {"
      "%0,%1,%2,%3,%4,%5,%6,%7,%8,%9,%10,%11,%12,%13,%14,%15,%16,%17,%18,%19,%20,%21,%22,%23,"
      "%24,%25,%26,%27,%28,%29,%30,%31,%32,%33,%34,%35,%36,%37,%38,%39,%40,%41,%42,%43,%44,%45,%46,%47,"
      "%48,%49,%50,%51,%52,%53,%54,%55"
      "}, %56, %57, p, 1, 1, 0, 1;}"
      : F40(0), F8(40), F8(48)
      : "l"(a), "l"(b), "r"(acc));
}
__device__ __forceinline__ void mma_n80(float* d, uint64_t a, uint64_t b, int acc) {
  asm volatile(
      "{.reg .pred p; setp.ne.b32 p, %42, 0;\n"
      "wgmma.mma_async.sync.aligned.m64n80k16.f32.bf16.bf16 {"
      "%0,%1,%2,%3,%4,%5,%6,%7,%8,%9,%10,%11,%12,%13,%14,%15,%16,%17,%18,%19,%20,%21,%22,%23,%24,%25,%26,%27,%28,%29,"
      "%30,%31,%32,%33,%34,%35,%36,%37,%38,%39}, %40, %41, p, 1, 1, 0, 1;}"
      : F40(0)
      : "l"(a), "l"(b), "r"(acc));
}
__device__ __forceinline__ void mma_qk_first(uint32_t* d, uint64_t a, uint64_t b) {
  asm volatile(
      "wgmma.mma_async.sync.aligned.m64n128k16.f16.f16.f16 {%0,%1,%2,%3,%4,%5,%6,%7,%8,%9,%10,%11,%12,%13,%14,%15,%16,%17,%18,%19,%20,%21,%22,%23,%24,%25,%26,%27,%28,%29,%30,%31}, %32, %33, 0, 1, 1, 0, 0;"
      : WU8(0), WU8(8), WU8(16), WU8(24)
      : "l"(a), "l"(b));
}
__device__ __forceinline__ void mma_qk_acc(uint32_t* d, uint64_t a, uint64_t b) {
  asm volatile(
      "wgmma.mma_async.sync.aligned.m64n128k16.f16.f16.f16 {%0,%1,%2,%3,%4,%5,%6,%7,%8,%9,%10,%11,%12,%13,%14,%15,%16,%17,%18,%19,%20,%21,%22,%23,%24,%25,%26,%27,%28,%29,%30,%31}, %32, %33, 1, 1, 1, 0, 0;"
      : RU8(0), RU8(8), RU8(16), RU8(24)
      : "l"(a), "l"(b));
}
__device__ __forceinline__ void mma_pv(uint32_t* d, const uint32_t* a, uint64_t b) {
  asm volatile("wgmma.mma_async.sync.aligned.m64n24k16.f16.f16.f16 {%0,%1,%2,%3,%4,%5}, {%6,%7,%8,%9}, %10, 1, 1, 1, 1;"
               : "+r"(d[0]), "+r"(d[1]), "+r"(d[2]), "+r"(d[3]), "+r"(d[4]), "+r"(d[5])
               : A4, "l"(b));
}
#define W4(o) "=f"(d[o + 0]), "=f"(d[o + 1]), "=f"(d[o + 2]), "=f"(d[o + 3])
__device__ __forceinline__ void mma_b48_rs0(float* d, const uint32_t* a, uint64_t b) {
  asm volatile("wgmma.mma_async.sync.aligned.m64n48k16.f32.bf16.bf16 {%0,%1,%2,%3,%4,%5,%6,%7,%8,%9,%10,%11,%12,%13,%14,%15,%16,%17,%18,%19,%20,%21,%22,%23}, {%24,%25,%26,%27}, %28, 0, 1, 1, 0;"
               : W4(0), W4(4), W4(8), W4(12), W4(16), W4(20)
               : A4, "l"(b));
}
__device__ __forceinline__ void mma_b48_rs(float* d, const uint32_t* a, uint64_t b) {
  asm volatile("wgmma.mma_async.sync.aligned.m64n48k16.f32.bf16.bf16 {%0,%1,%2,%3,%4,%5,%6,%7,%8,%9,%10,%11,%12,%13,%14,%15,%16,%17,%18,%19,%20,%21,%22,%23}, {%24,%25,%26,%27}, %28, 1, 1, 1, 0;"
               : F8(0), F8(8), F8(16)
               : A4, "l"(b));
}
__device__ __forceinline__ void mma_b8_rs0(float* d, const uint32_t* a, uint64_t b) {
  asm volatile("wgmma.mma_async.sync.aligned.m64n8k16.f32.bf16.bf16 {%0,%1,%2,%3}, {%4,%5,%6,%7}, %8, 0, 1, 1, 0;" : W4(0) : A4, "l"(b));
}
__device__ __forceinline__ void mma_b8_rs(float* d, const uint32_t* a, uint64_t b) {
  asm volatile("wgmma.mma_async.sync.aligned.m64n8k16.f32.bf16.bf16 {%0,%1,%2,%3}, {%4,%5,%6,%7}, %8, 1, 1, 1, 0;" : F4(0) : A4, "l"(b));
}
__device__ __forceinline__ uint32_t mul_b2(uint32_t a, uint32_t b) { uint32_t r; asm("mul.rn.bf16x2 %0, %1, %2;" : "=r"(r) : "r"(a), "r"(b)); return r; }
__device__ __forceinline__ void mma_b24_ss0(float* d, uint64_t a, uint64_t b) {
  asm volatile("wgmma.mma_async.sync.aligned.m64n24k16.f32.bf16.bf16 {%0,%1,%2,%3,%4,%5,%6,%7,%8,%9,%10,%11}, %12, %13, 0, 1, 1, 0, 0;"
               : W4(0), W4(4), W4(8)
               : "l"(a), "l"(b));
}
__device__ __forceinline__ void mma_b24_ss(float* d, uint64_t a, uint64_t b) {
  asm volatile("wgmma.mma_async.sync.aligned.m64n24k16.f32.bf16.bf16 {%0,%1,%2,%3,%4,%5,%6,%7,%8,%9,%10,%11}, %12, %13, 1, 1, 1, 0, 0;"
               : F4(0), F4(4), F4(8)
               : "l"(a), "l"(b));
}
__device__ __forceinline__ void mma_b24_tt0(float* d, uint64_t a, uint64_t b) {
  asm volatile("wgmma.mma_async.sync.aligned.m64n24k16.f32.bf16.bf16 {%0,%1,%2,%3,%4,%5,%6,%7,%8,%9,%10,%11}, %12, %13, 0, 1, 1, 1, 1;"
               : W4(0), W4(4), W4(8)
               : "l"(a), "l"(b));
}
__device__ __forceinline__ void mma_b24_tt(float* d, uint64_t a, uint64_t b) {
  asm volatile("wgmma.mma_async.sync.aligned.m64n24k16.f32.bf16.bf16 {%0,%1,%2,%3,%4,%5,%6,%7,%8,%9,%10,%11}, %12, %13, 1, 1, 1, 1, 1;"
               : F4(0), F4(4), F4(8)
               : "l"(a), "l"(b));
}

constexpr int G_XB = 16384, G_WB = 16384, G_PB = G_XB + 2 * G_WB;
constexpr int SM_STG = 3 * G_PB;
constexpr int SM_Q = 0, KV0 = 4 * SLICE;
constexpr int SM_PHI = KV0 + 4 * KVB;
constexpr int SM_AQ = KV0 + 14 * KVB;
constexpr int SM_MISC = SM_STG + 12 * SLICE;
constexpr int B_FULL = SM_MISC, B_EMPTY = B_FULL + 48, B_KV = B_EMPTY + 48, B_BD = B_KV + 256, B_QR = B_BD + 8, B_AV = B_QR + 8,
              B_AQ = B_AV + 8, B_KD = B_AQ + 8, B_QD = B_KD + 8, B_OF = B_QD + 8, B_OE = B_OF + 64, B_P = B_OE + 64;
constexpr int SM_FLAG = SM_MISC + 896;
constexpr int SM_WPHI = SM_MISC + 1024;
constexpr int SM_RED = SM_WPHI + 1536;
constexpr int SM_GATE = SM_RED + 256;
constexpr int SM_IND = SM_GATE + 2048;
constexpr int SM_KVI = SM_IND + 640;
constexpr int SM_ZERO = SM_KVI + 3840;
constexpr int SM_TOTAL = SM_ZERO + 1024;
constexpr int O_AB = 16384, O_WB = 10240, O_STB = O_AB + O_WB;
__host__ __device__ constexpr int o_slot(int i) { return SM_MISC - (i + 1) * O_STB; }

template <bool BR_B>
__device__ __forceinline__ void g_epilogue(float* acc, uint32_t stg, int ct, int w, int wp, int lane) {
  const int t = lane & 3, hf = (lane >> 3) & 1, csel = lane >> 4, r = lane & 7;
  const int Rw = w * 64 + wp * 16;
  const uint32_t offK = Rw * 16 + hf * 128 + r * 16, offV = (Rw / 8 + hf) * 384 + r * 16;
  const bool p0 = (PMASK >> (Rw / 8)) & 1, p1 = (PMASK >> (Rw / 8 + 1)) & 1;
  const bool lo = t < 2, ev = !(t & 1);
#pragma unroll
  for (int j = 0; j < 6; j++) {
    const int type = (ct * 12 + 2 * j) >> 5;
    float* a = acc + 20 * j;
    uint32_t aug0, aug1, q[10];
    if (BR_B) {
      const float s0 = type == 0 ? QSCALE : (type == 1 && p0) ? 0.001953125f : 1.f;
      const float s1 = type == 0 ? QSCALE : (type == 1 && p1) ? 0.001953125f : 1.f;
      aug0 = (type == 0 || !ev) ? 0u : (type == 1 && p0) ? 0x18001800u : 0x00003C00u;
      aug1 = (type == 0 || !ev) ? 0u : (type == 1 && p1) ? 0x18001800u : 0x00003C00u;
#pragma unroll
      for (int i = 0; i < 5; i++) { q[2 * i] = pack_h(a[4 * i] * s0, a[4 * i + 1] * s0); q[2 * i + 1] = pack_h(a[4 * i + 2] * s1, a[4 * i + 3] * s1); }
    } else {
      aug0 = aug1 = (type == 2 && ev) ? 0x00003F80u : 0u;
#pragma unroll
      for (int i = 0; i < 10; i++) q[i] = pack_b(a[2 * i], a[2 * i + 1]);
    }
    const uint32_t base = stg + 2 * j * SLICE + (type == 2 ? offV : offK);
    const uint32_t cs = type == 2 ? 128 : 2048;
    stsm4(base + csel * cs, q[0], q[1], q[2], q[3]);
    stsm4(base + 2 * cs + csel * SLICE, lo ? q[4] : aug0, lo ? q[5] : aug1, lo ? aug0 : q[4], lo ? aug1 : q[5]);
    stsm4(base + SLICE + csel * cs, q[6], q[7], q[8], q[9]);
  }
}

__device__ __forceinline__ uint32_t exp_mufu(uint32_t s) { uint32_t r; asm("ex2.approx.f16x2 %0, %1;" : "=r"(r) : "r"(s)); return r; }
__device__ __forceinline__ uint32_t hfma(uint32_t a, uint32_t b, uint32_t c) { uint32_t r; asm("fma.rn.f16x2 %0, %1, %2, %3;" : "=r"(r) : "r"(a), "r"(b), "r"(c)); return r; }
__device__ __forceinline__ uint32_t hfma_relu(uint32_t a, uint32_t b, uint32_t c) { uint32_t r; asm("fma.rn.relu.f16x2 %0, %1, %2, %3;" : "=r"(r) : "r"(a), "r"(b), "r"(c)); return r; }
#define D2(x) ((x) * 0x10001u)
__device__ __forceinline__ uint32_t exp_poly(uint32_t u, uint32_t zero) {
  uint32_t r = hfma_relu(u, D2(0x0200u), 0u);
  uint32_t f = hfma(r, D2(0xF800u), u);
  uint32_t w = hfma(f, D2(0x60fcu), D2(0x457fu));
  w = hfma(f, w, D2(0x27d8u));
  w = hfma_relu(f, w, D2(0x05a8u));
  return __funnelshift_l(zero, r, 10) + w;
}

__device__ __forceinline__ void phi_logits(float* d, uint32_t img16, uint32_t wphi16) {
  mma_b24_ss0(d, mkdesc(img16, 2048, 128, 0), mkdesc(wphi16, 384, 128, 0));
  mma_b24_ss(d, mkdesc(img16 + 128, 2048, 128, 0), mkdesc(wphi16 + 48, 384, 128, 0));
}
__device__ __forceinline__ void phi_exp(uint32_t* e, float* d, int t, uint32_t zero) {
  fence_f<12>(d);
#pragma unroll
  for (int i = 0; i < 12; i++) d[i] *= 1.4426950408889634f;
  const bool lo = t < 2;
  const uint32_t sgn = lo ? 0u : 0x80000000u;
#pragma unroll
  for (int hf = 0; hf < 2; hf++) {
    const float* x = d + 2 * hf;
    e[hf] = pack_b(ex2f(x[0]), ex2f(x[1])); e[2 + hf] = pack_b(ex2f(x[4]), ex2f(x[5]));
    e[4 + hf] = pack_b(ex2f(__uint_as_float(__float_as_uint(x[8]) ^ sgn)), ex2f(__uint_as_float(__float_as_uint(x[9]) ^ sgn)));
    e[6 + hf] = pack_b(ex2f(-x[0]), ex2f(-x[1])); e[10 + hf] = pack_b(ex2f(-x[4]), ex2f(-x[5]));
  }
  float am[3];
#pragma unroll
  for (int i = 0; i < 3; i++) am[i] = fmaxf(fmaxf(fabsf(d[4 * i]), fabsf(d[4 * i + 1])), fmaxf(fabsf(d[4 * i + 2]), fabsf(d[4 * i + 3])));
  if (!__all_sync(~0u, fmaxf(fmaxf(am[0], am[1]), am[2]) <= 40.f)) {
#pragma unroll
    for (int hf = 0; hf < 2; hf++) {
      const float* x = d + 2 * hf;
      float mx = fmaxf(fmaxf(fmaxf(x[0], x[1]), fmaxf(x[4], x[5])), fmaxf(x[8], x[9]));
      float mn = fminf(fminf(fminf(x[0], x[1]), fminf(x[4], x[5])), fminf(x[8], x[9]));
      mx = fmaxf(mx, __shfl_xor_sync(~0u, mx, 1)); mn = fminf(mn, __shfl_xor_sync(~0u, mn, 1));
      mx = fmaxf(mx, __shfl_xor_sync(~0u, mx, 2)); mn = fminf(mn, __shfl_xor_sync(~0u, mn, 2));
      e[hf] = pack_b(ex2f(x[0] - mx), ex2f(x[1] - mx)); e[2 + hf] = pack_b(ex2f(x[4] - mx), ex2f(x[5] - mx));
      e[4 + hf] = pack_b(ex2f(lo ? x[8] - mx : mn - x[8]), ex2f(lo ? x[9] - mx : mn - x[9]));
      e[6 + hf] = pack_b(ex2f(mn - x[0]), ex2f(mn - x[1])); e[10 + hf] = pack_b(ex2f(mn - x[4]), ex2f(mn - x[5]));
    }
  }
  e[8] = zero; e[9] = zero;
  fence_u<12>(e);
}

__device__ __forceinline__ void phi_out(uint32_t* v, float* d, const float* gate, int src) {
  fence_f<24>(d);
#pragma unroll
  for (int hf = 0; hf < 2; hf++) {
    const float rp = __fdividef(1.f, d[9 + 2 * hf]), rn = __fdividef(1.f, d[21 + 2 * hf]);
    const float sc = __fdividef(gate[8 * hf], fmaf(d[8 + 2 * hf], rp, fmaf(d[20 + 2 * hf], rn, 1e-6f)));
    const float a = __shfl_sync(~0u, rp * sc, src), b = __shfl_sync(~0u, rn * sc, src);
#pragma unroll
    for (int c = 0; c < 3; c++)
      v[2 * c + hf] = pack_b(fmaf(d[12 + 4 * c + 2 * hf], b, d[4 * c + 2 * hf] * a), fmaf(d[13 + 4 * c + 2 * hf], b, d[4 * c + 2 * hf + 1] * a));
  }
}

__device__ __forceinline__ void store_o(const uint32_t* v, int cbase, int h, int row, int t) {
  uint32_t* p = (uint32_t*)(g_o + ((row >> 7) * 160 + cbase + (h >> 1) * 5) * 2048 + (row & 127) * 16) + t;
  uint32_t* p0 = p + ((h & 1) ? 1536 : 0);
  p0[0] = v[0]; p0[32] = v[1]; p0[512] = v[2]; p0[544] = v[3];
  if ((t >> 1) == (h & 1)) { p[1024] = v[4]; p[1056] = v[5]; }
}

__device__ __noinline__ void attn_fallback(const uint32_t* flags, int h, int part, const __nv_bfloat16* x, const __nv_bfloat16* wB) {
  __nv_bfloat16* kv = g_fb + (size_t)h * S_ * 40;
  const int tid = fresh_tid() - 256;
  for (int i = tid; i < S_ * 40; i += 256) {
    const int tok = i / 40, c = i % 40;
    const __nv_bfloat16* xr = x + (size_t)tok * D_;
    const __nv_bfloat16* wc = wB + (c < 20 ? 640 + h * 20 + c : 1280 + h * 20 + c - 20);
    float acc = 0.f;
    for (int k = 0; k < D_; k++) acc += __bfloat162float(xr[k]) * __bfloat162float(wc[(size_t)k * 1920]);
    kv[i] = __float2bfloat16(acc);
  }
  bar_sync(12, 256);
  const int warp = tid >> 5, lane = tid & 31;
  for (int wt = warp; wt < 32; wt += 8) {
    if (!flags[wt]) continue;
    for (int rr = 0; rr < 16; rr++) {
      const int row = part * 512 + wt * 16 + rr;
      float qv = 0.f;
      if (lane < 20) {
        for (int k = 0; k < D_; k++) qv += __bfloat162float(x[(size_t)row * D_ + k]) * __bfloat162float(wB[(size_t)k * 1920 + h * 20 + lane]);
        qv = __bfloat162float(__float2bfloat16(qv));
      }
      float m = -INFINITY, l = 0.f, o[20];
#pragma unroll
      for (int d = 0; d < 20; d++) o[d] = 0.f;
      for (int j = lane; j < S_; j += 32) {
        float s = 0.f;
#pragma unroll
        for (int d = 0; d < 20; d++) s += __shfl_sync(~0u, qv, d) * __bfloat162float(kv[j * 40 + d]);
        s = __bfloat162float(__float2bfloat16(__bfloat162float(__float2bfloat16(s)) * 0.22360679775f)) * 1.4426950408889634f;
        const float mn = fmaxf(m, s), c = exp2f(m - mn), p = exp2f(s - mn);
        l = l * c + p;
#pragma unroll
        for (int d = 0; d < 20; d++) o[d] = o[d] * c + p * __bfloat162float(kv[j * 40 + 20 + d]);
        m = mn;
      }
      float mg = m;
#pragma unroll
      for (int of = 16; of; of >>= 1) mg = fmaxf(mg, __shfl_xor_sync(~0u, mg, of));
      const float c = exp2f(m - mg);
      l *= c;
#pragma unroll
      for (int of = 16; of; of >>= 1) l += __shfl_xor_sync(~0u, l, of);
      const float sc = (1.f - __ldcg(g_gate + row)) / l;
#pragma unroll
      for (int d = 0; d < 20; d++) {
        float v = o[d] * c;
#pragma unroll
        for (int of = 16; of; of >>= 1) v += __shfl_xor_sync(~0u, v, of);
        const int col = h * 20 + d;
        if (lane == 0) *(__nv_bfloat16*)(g_o + ((size_t)(row >> 7) * 160 + 80 + (col >> 3)) * 2048 + (row & 127) * 16 + (col & 7) * 2) = __float2bfloat16(v * sc);
      }
    }
  }
  bar_sync(12, 256);
}

__device__ __forceinline__ void prep_q(uint8_t* sm, uint32_t sb, int i, int odd) {
  const uint32_t st = ((const uint32_t*)(sm + SM_RED))[i & 31];
  const float kn2 = __uint_as_float(__reduce_max_sync(~0u, (i & 16) ? 0u : st)), vmx = __uint_as_float(__reduce_max_sync(~0u, (i & 16) ? st : 0u));
  const bool head_ok = kn2 <= 1048576.f && vmx <= 32768.f && vmx >= 0.00390625f;
#pragma unroll
  for (int u = 0; u < 2; u++) {
    const int row = i + 256 * u;
    const uint32_t ad = sb + SM_Q + (row >> 7) * SLICE + (row & 127) * 16;
    const uint4 c0 = lds128(ad), c1 = lds128(ad + 2048), c2 = lds128(ad + 4096);
    const uint32_t v[12] = {c0.x, c0.y, c0.z, c0.w, c1.x, c1.y, c1.z, c1.w, c2.x, c2.y, c2.z, c2.w};
    float n0 = 0.f, n1 = 0.f;
#pragma unroll
    for (int c = 0; c < 12; c++) { const float2 a = __half22float2(*(const __half2*)&v[c]); n0 = fmaf(a.x, a.x, n0); n1 = fmaf(a.y, a.y, n1); }
    n0 += n1;
    float r;
    asm("sqrt.approx.f32 %0, %1;" : "=f"(r) : "f"(n0 * kn2));
    const float b = r * 1.01f + 0.05f;
    *(uint32_t*)(sm + SM_Q + (row >> 7) * SLICE + 4096 + (row & 127) * 16 + (odd ? 0 : 8)) = pack_h(-fmaxf(0.f, ceilf(b * 8.f - 126.f) * 0.125f), 13.5f);
    if (!(head_ok && b <= 30.f && n0 <= 1048576.f)) ((volatile uint32_t*)(sm + SM_FLAG))[row >> 4] = 1;
  }
}

struct Params {
  CUtensorMap tmX, tmWB, tmWA, tmOut;
  const __nv_bfloat16 *x, *gate_w, *w_phi, *wB, *woA, *woB;
};

__device__ __forceinline__ void agent_g(const Params& P, uint32_t sb) {
  const int bid = blockIdx.x, rank = bid & 1, lane = threadIdx.x & 31;
  const int pr = bid >> 1, rt = (pr & 7) * 2 + rank, ct = pr >> 3, h = bid >> 2, part = bid & 3;
  {
    int s = 2, ph = 0;
#pragma unroll 1
    for (int it = 6; it < 40; it++) {
      const int kb = it >= 20 ? it - 20 : it;
      const uint32_t st = sb + (s >> 1) * G_PB + G_XB + (s & 1) * G_WB + rank * 8192, fb = sb + B_FULL + 8 * s;
      const CUtensorMap* wm = it >= 20 ? &P.tmWA : &P.tmWB;
      mbar_wait_z(sb + B_EMPTY + 8 * s, ph);
      if (elect_one()) {
        mbar_expect_tx(fb, (s & 1) ? G_WB : G_XB + G_WB);
        if (s & 1) tma2d(sb + (s >> 1) * G_PB, &P.tmX, (kb - 1) * 32, rt * 128, fb - 8);
        tma2d_mc(st, wm, ct * 240 + rank * 128, kb * 32, fb, 3);
        tma2d_mc(st + 4096, wm, ct * 240 + rank * 128 + 64, kb * 32, fb, 3);
      }
      if (s == 1) ph ^= 1;
      if (++s == 6) s = 0;
    }
  }
  const uint8_t* kvsrc = g_kvB + (size_t)h * 16 * KVB;
  await(C_B, 128);
  mbar_wait_z(sb + B_EMPTY + 8, 1);
  if (elect_one()) {
    fence_async_g();
    mbar_expect_tx(sb + B_BD, 4 * SLICE + 2048 + 128);
    bulk_g2s(sb + SM_Q, g_qB + ((size_t)h * 16 + part * 4) * SLICE, 4 * SLICE, sb + B_BD);
    bulk_g2s(sb + SM_RED, g_stat + h * 32, 128, sb + B_BD);
    bulk_g2s(sb + SM_GATE, g_gate + part * 512, 2048, sb + B_BD);
#pragma unroll
    for (int j = 0; j < 2; j++) { mbar_expect_tx(sb + B_KV + 8 * j, KVB); bulk_g2s(sb + KV0 + j * KVB, kvsrc + j * KVB, KVB, sb + B_KV + 8 * j); }
  }
#pragma unroll
  for (int q = 1; q < 3; q++) {
    mbar_wait_z(sb + B_EMPTY + 16 * q + 8, 0);
    if (elect_one()) {
#pragma unroll
      for (int j = 4 * q - 2; j < 4 * q + 2; j++) { mbar_expect_tx(sb + B_KV + 8 * j, KVB); bulk_g2s(sb + KV0 + j * KVB, kvsrc + j * KVB, KVB, sb + B_KV + 8 * j); }
    }
  }
  bar_sync(9, 288);
  if (lane == 0) {
#pragma unroll
    for (int q = 0; q < 12; q++) bulk_s2g(g_A + ((size_t)(ct * 12 + q) * 16 + rt) * SLICE, sb + SM_STG + q * SLICE, SLICE);
    bulk_commit();
    bulk_wait_all();
  }
  __syncwarp();
  if (elect_one()) {
#pragma unroll
    for (int j = 10; j < 16; j++) { mbar_expect_tx(sb + B_KV + 8 * j, KVB); bulk_g2s(sb + KV0 + j * KVB, kvsrc + j * KVB, KVB, sb + B_KV + 8 * j); }
  }
  if (lane == 0) signal(C_A + bid * 8);
  {
    const int l12 = lane % 12, c2 = ((l12 >> 2) * 32 + h) / 12, r2 = part * 4 + (l12 & 3);
    await_all(C_A + (((c2 * 8 + (r2 >> 1)) << 1) | (r2 & 1)) * 8, 1);
  }
  mbar_wait_z(sb + B_P + 16 * 2, 0);
  if (elect_one()) {
    fence_async_g();
    mbar_expect_tx(sb + B_AV, 8 * SLICE);
#pragma unroll
    for (int q = 0; q < 4; q++) {
      bulk_g2s(sb + KV0 + q * KVB + SLICE, g_A + ((size_t)(H_ + h) * 16 + part * 4 + q) * SLICE, SLICE, sb + B_AV);
      bulk_g2s(sb + KV0 + q * KVB, g_A + ((size_t)(2 * H_ + h) * 16 + part * 4 + q) * SLICE, SLICE, sb + B_AV);
    }
  }
  mbar_wait_z(sb + B_P + 16 * 3, 0);
}

__device__ __forceinline__ void branch_a(uint8_t* sm, uint32_t sb) {
  const int tid = fresh_tid(), bid = fresh_bid(), lane = tid & 31, g = lane >> 2, t = lane & 3;
  const int wp = __shfl_sync(~0u, (tid >> 5) & 3, 0), h = bid >> 2, part = bid & 3;
  const uint32_t sl = sb & 0x3FFFF, wphi16 = (sl + SM_WPHI) >> 4;
  const uint32_t zero = *(volatile uint32_t*)(sm + SM_ZERO);
  {
    const uint32_t ad = sb + SM_PHI + (wp * 2 + ((lane >> 3) & 1)) * 640 + (lane >> 4) * 128 + (lane & 7) * 16;
    const uint32_t ind16 = (sl + SM_IND) >> 4;
    float* dst = g_kvs + h * 960 + (wp * 16 + g) * 24 + 2 * t;
    mbar_wait_z(sb + B_AV, 0);
    float d[12];
    wg_fence();
    phi_logits(d, (sl + KV0 + SLICE) >> 4, wphi16);
    wg_commit();
    wg_wait<0>();
#pragma unroll 1
    for (int i = 0; i < 8; i++) {
      const uint32_t unit = sl + KV0 + (i >> 1) * KVB, buf = (i & 3) * 5120;
      {
        uint32_t e[12];
        phi_exp(e, d, t, zero);
        float z[4];
        const int nx = min(i + 1, 7);
        wg_fence();
        mma_b8_rs0(z, e, mkdesc(ind16, 128, 128, 0));
        mma_b8_rs(z, e + 4, mkdesc(ind16 + 16, 128, 128, 0));
        mma_b8_rs(z, e + 8, mkdesc(ind16 + 24, 128, 128, 0));
        phi_logits(d, (sl + KV0 + (nx >> 1) * KVB + SLICE + (nx & 1) * 1024) >> 4, wphi16);
        wg_commit();
        wg_wait<0>();
        fence_f<4>(z); fence_u<12>(e);
        uint32_t r[2];
#pragma unroll
        for (int hf = 0; hf < 2; hf++) r[hf] = __shfl_sync(~0u, pack_b(__fdividef(1.f, z[2 * hf]), __fdividef(1.f, z[2 * hf + 1])), lane & ~3);
        const uint32_t p0 = __byte_perm(r[0], 0, 0x1010), p1 = __byte_perm(r[1], 0, 0x1010), n0 = __byte_perm(r[0], 0, 0x3232), n1 = __byte_perm(r[1], 0, 0x3232);
        stsm4(ad + buf, mul_b2(e[0], p0), mul_b2(e[1], p1), mul_b2(e[2], p0), mul_b2(e[3], p1));
        stsm4(ad + buf + 256, mul_b2(e[4], t < 2 ? p0 : n0), mul_b2(e[5], t < 2 ? p1 : n1), mul_b2(e[6], n0), mul_b2(e[7], n1));
        stsm2(ad + buf + 512, mul_b2(e[10], n0), mul_b2(e[11], n1));
      }
      if ((i & 3) == 3) {
        fence_async();
        bar_sync(11, 128);
        float kv[12];
        wg_fence();
        mma_b24_tt0(kv, mkdesc((sl + SM_PHI) >> 4, 640, 128, 0), mkdesc((unit - KVB) >> 4, 384, 128, 0));
#pragma unroll
        for (int k = 1; k < 16; k++)
          mma_b24_tt(kv, mkdesc(((sl + SM_PHI) >> 4) + k * 80, 640, 128, 0), mkdesc(((unit - KVB + (k >> 3) * KVB) >> 4) + (k & 7) * 48, 384, 128, 0));
        wg_commit();
        wg_wait<0>();
        fence_f<12>(kv);
        if (wp < 3) {
#pragma unroll
          for (int c = 0; c < 3; c++) asm volatile("red.relaxed.gpu.global.add.v2.f32 [%0], {%1,%2};" ::"l"(dst + 8 * c), "f"(kv[4 * c]), "f"(kv[4 * c + 1]) : "memory");
        }
        if (wp < 2) {
#pragma unroll
          for (int c = 0; c < 3; c++) asm volatile("red.relaxed.gpu.global.add.v2.f32 [%0], {%1,%2};" ::"l"(dst + 192 + 8 * c), "f"(kv[4 * c + 2]), "f"(kv[4 * c + 3]) : "memory");
        }
        if (i == 3) bar_sync(11, 128);
      }
    }
    bar_sync(11, 128);
    if (tid == 608) signal(C_KV + h * 32);
    if (wp == 0) {
      if (elect_one()) {
        const uint8_t* kvsrc = g_kvB + (size_t)h * 16 * KVB;
#pragma unroll
        for (int j = 5; j >= 0; j--) { mbar_expect_tx(sb + B_KV + 248 - 8 * j, KVB); bulk_g2s(sb + KV0 + j * KVB, kvsrc + j * KVB, KVB, sb + B_KV + 248 - 8 * j); }
      }
      mbar_wait_z(sb + B_P + 16 * 9, 0);
      if (elect_one()) {
        mbar_expect_tx(sb + B_AQ, 4 * SLICE);
        bulk_g2s(sb + SM_AQ, g_A + ((size_t)h * 16 + part * 4) * SLICE, 4 * SLICE, sb + B_AQ);
      }
      await(C_KV + h * 32, 4);
    }
    bar_sync(11, 128);
  }
  const int zc = (h & 1) ? 16 : 20;
#pragma unroll
  for (int u = 0; u < 2; u++) {
    const int j = (tid & 127) + 128 * u, fc = j / 48, n = j % 48, dd = n % 24;
    if (j < 240) {
      const float* kvs = g_kvs + h * 960 + fc * 192 + dd;
      uint32_t w[4];
#pragma unroll
      for (int c = 0; c < 4; c++) w[c] = dd == zc + 1 ? 0x3F803F80u : pack_b(__ldcg(kvs + 48 * c), __ldcg(kvs + 48 * c + 24));
      const bool neg = n >= 24, k0 = (fc > 2) == neg, k1 = (fc > 1) == neg;
      *(uint4*)(sm + SM_KVI + j * 16) = make_uint4(k0 ? w[0] : 0u, k0 ? w[1] : 0u, k1 ? w[2] : 0u, k1 ? w[3] : 0u);
    }
  }
  fence_async();
  __syncwarp();
  if (lane == 0) mbar_arrive(sb + B_KD);
}

__device__ __forceinline__ void agent_t(uint32_t sb) {
  const int bid = fresh_bid(), rank = bid & 1, lane = fresh_tid() & 31, part = bid & 3;
  mbar_wait_z(sb + B_QD, 0);
  if (lane == 0) signal(C_OA + part * 32);
  const uint8_t* osrc = g_o + (size_t)(bid >> 3) * 160 * 2048;
  const uint8_t* wsrc = g_wo + (bid & 7) * 204800;
  await(C_OA + (bid >> 5) * 32, 32);
  mbar_wait_z(sb + B_P + 16 * 13, 0);
  if (elect_one()) {
    fence_async_g();
#pragma unroll
    for (int it = 0; it < 4; it++) {
      mbar_expect_tx(sb + B_OF + 8 * it, O_STB);
      bulk_g2s(sb + o_slot(it) + O_AB, wsrc + it * O_WB, O_WB, sb + B_OF + 8 * it);
      bulk_g2s(sb + o_slot(it), osrc + it * O_AB, O_AB, sb + B_OF + 8 * it);
    }
  }
  mbar_wait_z(sb + B_P + 16 * 15, 0);
  if (elect_one()) {
#pragma unroll
    for (int it = 4; it < 6; it++) {
      mbar_expect_tx(sb + B_OF + 8 * it, O_STB);
      bulk_g2s(sb + o_slot(it) + O_AB, wsrc + it * O_WB, O_WB, sb + B_OF + 8 * it);
      bulk_g2s(sb + o_slot(it), osrc + it * O_AB, O_AB, sb + B_OF + 8 * it);
    }
  }
#pragma unroll
  for (int it = 6; it < 13; it++) {
    const uint32_t st = sb + o_slot(it & 7), fb = sb + B_OF + 8 * (it & 7);
    mbar_wait_z(sb + B_OE + 8 * (it & 7), it >= 14);
    if (elect_one()) {
      mbar_expect_tx(fb, O_STB);
      if (it < 10) bulk_g2s_mc(st + rank * 8192, osrc + it * O_AB + rank * 8192, 8192, fb, 3);
      bulk_g2s(st + O_AB, wsrc + it * O_WB, O_WB, fb);
    }
  }
  const int ob = C_OB + (bid >> 5) * 8 + lane * 32;
  uint32_t ready = 0;
#pragma unroll
  for (int it = 10; it < 20; it++) {
    const uint32_t st = sb + o_slot(it & 7), fb = sb + B_OF + 8 * (it & 7);
    const int h0 = (it - 10) * 64 / 20, h1 = ((it - 10) * 64 + 63) / 20;
    const uint32_t need = (uint32_t)((2ull << h1) - (1ull << h0));
    if (it >= 13) {
      mbar_wait(sb + B_OE + 8 * (it & 7), it >= 14);
      if (elect_one()) { mbar_expect_tx(fb, O_STB); bulk_g2s(st + O_AB, wsrc + it * O_WB, O_WB, fb); }
    }
    if ((ready & need) != need) { ready = await_mask(ob, need); fence_async_g(); }
    if (elect_one()) {
      bulk_g2s_mc(st + rank * 8192, osrc + it * O_AB + rank * 8192, 8192, fb, 3);
    }
  }
  uint32_t v = 0;
  if (lane == 0) v = atomicAdd(&g_cnt[C_EXIT], 1u);
  if (__shfl_sync(~0u, v, 0) == 127u) {
    g_cnt[C_KV + 32 * lane] = 0;
    if (lane < 7) g_cnt[32 * lane] = 0;
#pragma unroll
    for (int i = 0; i < 4; i++) { g_cnt[C_A + 8 * (lane + 32 * i)] = 0; g_cnt[C_OB + 8 * (lane + 32 * i)] = 0; }
  }
}

__global__ void __cluster_dims__(2, 1, 1) __launch_bounds__(640, 1) fused_kernel(const __grid_constant__ Params P) {
  extern __shared__ __align__(1024) uint8_t sm[];
  const uint32_t sb = __shfl_sync(~0u, smem_u32(sm), 0), sl = sb & 0x3FFFF;
  const int tid = fresh_tid(), wg = __shfl_sync(~0u, tid >> 7, 0), wp = __shfl_sync(~0u, (tid >> 5) & 3, 0), lane = tid & 31;
  const int bid = blockIdx.x;
  if (wg == 4 && wp == 0) {
    const int rank = bid & 1, rt = ((bid >> 1) & 7) * 2 + rank, ct = bid >> 4;
    if (elect_one()) {
      asm volatile("prefetch.tensormap [%0];" ::"l"(&P.tmWB) : "memory");
#pragma unroll
      for (int i = 0; i < 6; i++) mbar_init(sb + B_FULL + 8 * i, 1);
#pragma unroll
      for (int it = 0; it < 6; it++) {
        const int s = (it + 2) % 6;
        mbar_expect_tx(sb + B_FULL + 8 * s, (it & 1) ? G_WB : G_XB + G_WB);
        if (!(it & 1)) tma2d(sb + (s >> 1) * G_PB, &P.tmX, it * 32, rt * 128, sb + B_FULL + 8 * s);
      }
#pragma unroll
      for (int i = 0; i < 6; i++) mbar_init(sb + B_EMPTY + 8 * i, 4);
      mbar_init(sb + B_BD, 1); mbar_init(sb + B_QR, 8);
    }
    __syncwarp();
    asm volatile("barrier.cluster.arrive.release.aligned;" ::: "memory");
    asm volatile("barrier.cluster.wait.aligned;" ::: "memory");
    if (elect_one()) {
#pragma unroll
      for (int it = 0; it < 6; it++) {
        const int s = (it + 2) % 6;
        const uint32_t st = sb + (s >> 1) * G_PB + G_XB + (s & 1) * G_WB + rank * 8192, fb = sb + B_FULL + 8 * s;
        tma2d_mc(st, &P.tmWB, ct * 240 + rank * 128, it * 32, fb, 3);
        tma2d_mc(st + 4096, &P.tmWB, ct * 240 + rank * 128 + 64, it * 32, fb, 3);
      }
      asm volatile("prefetch.tensormap [%0];" ::"l"(&P.tmWA) : "memory");
    }
    __syncwarp();
  } else {
    asm volatile("barrier.cluster.arrive.relaxed.aligned;" ::: "memory");
    asm volatile("barrier.cluster.wait.aligned;" ::: "memory");
  }
  if (wg == 4) {
    asm volatile("setmaxnreg.dec.sync.aligned.u32 32;");
    if (wp == 0) agent_g(P, sb);
    bar_sync(11, 128);
    asm volatile("setmaxnreg.inc.sync.aligned.u32 64;");
    branch_a(sm, sb);
    if (wp == 0) agent_t(sb);
    return;
  }
  {
    const int pr = bid >> 1, rt = (pr & 7) * 2 + (bid & 1), ct = pr >> 3;
    const int h = bid >> 2, part = bid & 3, odd = h & 1;
    const uint32_t stg = sb + SM_STG;
    if (wg < 2) {
      asm volatile("setmaxnreg.inc.sync.aligned.u32 168;");
      float acc[120];
      int s = 2, ph = 0;
#pragma unroll 1
      for (int round = 0; round < 2; round++) {
        int prev = 0;
#pragma unroll 1
        for (int kb = 0; kb < 20; kb++) {
          mbar_wait(sb + B_FULL + 8 * s, ph);
          const uint32_t xa = (sl + (s >> 1) * G_PB + wg * 8192 + (s & 1) * 64) >> 4, wa = (sl + (s >> 1) * G_PB + G_XB + (s & 1) * G_WB) >> 4;
          wg_fence();
#pragma unroll
          for (int k = 0; k < 2; k++) {
            mma_n128(acc, mkdesc(xa + 2 * k, 16, 1024, 1), mkdesc(wa + 128 * k, 4096, 1024, 1), (kb | k) != 0);
            mma_n112(acc + 64, mkdesc(xa + 2 * k, 16, 1024, 1), mkdesc(wa + 512 + 128 * k, 4096, 1024, 1), (kb | k) != 0);
          }
          wg_commit();
          if (kb > 0) {
            wg_wait<1>();
            if ((tid & 127) < 2) mbar_arrive_cluster(sb + B_EMPTY + 8 * prev, tid & 1);
          }
          prev = s;
          if (s == 1) ph ^= 1;
          if (++s == 6) s = 0;
        }
        wg_wait<0>();
        fence_f<120>(acc);
        if ((tid & 127) < 2) mbar_arrive_cluster(sb + B_EMPTY + 8 * prev, tid & 1);
        if (round == 0) {
          g_epilogue<true>(acc, stg, ct, wg, wp, lane);
          fence_async();
          bar_arrive(1, 416);
        } else {
          bar_sync(2, 416);
          g_epilogue<false>(acc, stg, ct, wg, wp, lane);
          fence_async();
          bar_arrive(9, 288);
        }
      }
      asm volatile("setmaxnreg.dec.sync.aligned.u32 104;");
    } else {
      asm volatile("setmaxnreg.dec.sync.aligned.u32 56;");
      const int i8 = tid - 256;
      {
        uint4 v[4];
        uint32_t off[4];
#pragma unroll
        for (int u = 0; u < 4; u++) {
          const uint32_t c = bid * 100 + min((i8 >> 3) + 32 * u, 99), grp = c / 80, pc = c - grp * 80, k = grp * 8 + (i8 & 7), cb = pc / 10;
          v[u] = __ldg((const uint4*)(k < 640 ? P.woA + k * 640 : P.woB + (k - 640) * 640) + pc);
          off[u] = cb * (204800 - 1280) + pc * 128 + grp * 1280 + (i8 & 7) * 16;
        }
        if (wg == 2 && wp < 3) {
          const int kc = i8 / 24, f = i8 - kc * 24, d0 = kc == 3 ? (odd ? -4 : 16) : kc * 8 + odd * 4;
          const uint16_t* wsrc = (const uint16_t*)P.w_phi + h * 400 + d0 * 20 + (f < 20 ? f : f - 4);
          const bool lo = kc < 2 || (kc == 3 && !odd), hi = kc < 2 || (kc == 3 && odd);
          uint32_t w[8];
#pragma unroll
          for (int e = 0; e < 8; e++) w[e] = (e < 4 ? lo : hi) ? __ldg(wsrc + e * 20) : 0u;
          *(uint4*)(sm + SM_WPHI + i8 * 16) = make_uint4(w[0] | w[1] << 16, w[2] | w[3] << 16, w[4] | w[5] << 16, w[6] | w[7] << 16);
        } else if (wg == 2) {
          ((uint32_t*)(sm + SM_FLAG))[i8 - 96] = 0;
          if (elect_one()) {
#pragma unroll
            for (int i = 0; i < 32; i++) mbar_init(sb + B_KV + 8 * i, 1);
#pragma unroll
            for (int i = 16; i < 26; i++) mbar_arrive(sb + B_KV + 8 * i);
            mbar_init(sb + B_AV, 1); mbar_init(sb + B_AQ, 1); mbar_init(sb + B_KD, 4); mbar_init(sb + B_QD, 16);
#pragma unroll
            for (int i = 0; i < 16; i++) mbar_init(sb + B_P + 16 * i, 16);
#pragma unroll
            for (int i = 0; i < 8; i++) { mbar_init(sb + B_OF + 8 * i, 1); mbar_init(sb + B_OE + 8 * i, 4); }
            asm volatile("fence.mbarrier_init.release.cluster;" ::: "memory");
          }
        } else {
          const int t7 = i8 - 128;
          ((uint2*)(sm + SM_ZERO))[t7] = make_uint2(0u, 0u);
          if (t7 < 80) {
            const int fc = t7 >> 4, n = (t7 >> 1) & 7, neg = (t7 & 1) ? fc > 1 : fc > 2;
            const uint32_t w = n == neg ? 0x3F803F80u : 0u;
            ((uint2*)(sm + SM_IND))[t7] = make_uint2(w, w);
          }
        }
        if (part == 0 && i8 < 240) ((float4*)g_kvs)[h * 240 + i8] = make_float4(0.f, 0.f, 0.f, 0.f);
        fence_async();
#pragma unroll
        for (int u = 0; u < 4; u++) *(uint4*)(g_wo + off[u]) = v[u];
      }
      {
        const int row = bid * 16 + (i8 >> 5) * 2;
        float z0 = 0.f, z1 = 0.f;
#pragma unroll
        for (int i = 0; i < 3; i++) {
          if (lane + 32 * i < 80) {
            const uint4 gw = __ldg((const uint4*)P.gate_w + lane + 32 * i);
            const uint4 a = __ldg((const uint4*)(P.x + row * D_) + lane + 32 * i), b = __ldg((const uint4*)(P.x + (row + 1) * D_) + lane + 32 * i);
            const uint32_t gv[4] = {gw.x, gw.y, gw.z, gw.w}, av[4] = {a.x, a.y, a.z, a.w}, bv[4] = {b.x, b.y, b.z, b.w};
#pragma unroll
            for (int e = 0; e < 4; e++) {
              const float gl = bf_lo(gv[e]), gh = bf_hi(gv[e]);
              z0 = fmaf(bf_lo(av[e]), gl, fmaf(bf_hi(av[e]), gh, z0));
              z1 = fmaf(bf_lo(bv[e]), gl, fmaf(bf_hi(bv[e]), gh, z1));
            }
          }
        }
        float z = (lane & 1) ? z1 : z0;
        z += __shfl_xor_sync(~0u, (lane & 1) ? z0 : z1, 1);
#pragma unroll
        for (int o = 16; o > 1; o >>= 1) z += __shfl_xor_sync(~0u, z, o);
        if (lane < 2) g_gate[row + lane] = __fdividef(1.f, 1.f + __expf(-z));
      }
      if (wg == 3) {
        const int t7 = tid & 127;
        bar_sync(1, 416);
        const bool pl = (PMASK >> (t7 >> 3)) & 1;
#pragma unroll 2
        for (int q = 0; q < 12; q++) {
          const int sidx = ct * 12 + q, type = sidx >> 5;
          if (type == 0) continue;
          const uint32_t ad = stg + q * SLICE + (type == 1 ? t7 * 16 : (t7 >> 3) * 384 + (t7 & 7) * 16), cs = type == 1 ? 2048 : 128;
          const uint4 c0 = lds128(ad), c1 = lds128(ad + cs), c2 = lds128(ad + 2 * cs);
          const uint32_t v[10] = {c0.x, c0.y, c0.z, c0.w, c1.x, c1.y, c1.z, c1.w, (q & 1) ? c2.z : c2.x, (q & 1) ? c2.w : c2.y};
          float r;
          if (type == 1) {
            float r1 = 0.f;
            r = 0.f;
#pragma unroll
            for (int i = 0; i < 10; i++) { const float2 f = __half22float2(*(const __half2*)&v[i]); r = fmaf(f.x, f.x, r); r1 = fmaf(f.y, f.y, r1); }
            r += r1;
            if (pl) r *= 262144.f;
          } else {
            uint32_t m = 0;
#pragma unroll
            for (int i = 0; i < 10; i++) m = __vmaxu2(m, v[i] & 0x7fff7fffu);
            m = max(m & 0xffffu, m >> 16);
            r = __half2float(__ushort_as_half((unsigned short)m));
          }
          const uint32_t u = __reduce_max_sync(~0u, __float_as_uint(r));
          if (lane == 0) ((uint32_t*)(sm + SM_RED))[q * 4 + wp] = u;
        }
        bar_arrive(2, 416);
        bar_sync(7, 128);
        if (t7 < 12) {
          const int sidx = ct * 12 + t7, type = sidx >> 5, head = sidx & 31;
          const uint4 u = *(const uint4*)(sm + SM_RED + t7 * 16);
          if (type != 0) g_stat[head * 32 + (type - 1) * 16 + rt] = __uint_as_float(max(max(u.x, u.y), max(u.z, u.w)));
        }
        fence_async();
        bar_arrive(3, 256);
      } else if (wp == 1) {
        bar_sync(1, 416);
        if (lane == 0) {
#pragma unroll 1
          for (int q = 0; q < 12; q++) {
            const int sidx = ct * 12 + q, type = sidx >> 5, head = sidx & 31;
            bulk_s2g(type == 0 ? g_qB + ((size_t)head * 16 + rt) * SLICE : g_kvB + ((size_t)head * 16 + rt) * KVB + (type - 1) * SLICE, stg + q * SLICE, SLICE);
            bulk_commit();
            asm volatile("cp.async.bulk.wait_group 1;" ::: "memory");
          }
          bulk_wait_all();
        }
        __syncwarp();
        bar_arrive(2, 416);
        bar_sync(3, 256);
        if (lane == 0) signal(C_B);
        __syncwarp();
      } else {
        bar_arrive(3, 256);
      }
      mbar_wait(sb + B_BD, 0);
      prep_q(sm, sb, tid - 256, odd);
      fence_async();
      __syncwarp();
      if (lane == 0) mbar_arrive(sb + B_QR);
      asm volatile("setmaxnreg.inc.sync.aligned.u32 104;");
    }
  }
  uint32_t oh[6], s[32], p[32];
  float o[12];
  mbar_wait(sb + B_QR, 0);
  const uint32_t zero = *(volatile uint32_t*)(sm + SM_ZERO);
#pragma unroll
  for (int i = 0; i < 12; i++) o[i] = 0.f;
  const uint32_t stops = 0x8480u;
#pragma unroll 1
  for (int j0 = 0; j0 < 16;) {
    const int jj = j0 + __ffs(stops >> j0) - 1;
    uint32_t bar = sb + B_KV + 16 * j0;
    const uint32_t k16 = (sl + KV0 + (j0 < 8 ? 2 * j0 : 31 - 2 * j0) * KVB) >> 4;
    const uint32_t qoff = SM_Q + wg * SLICE + (j0 >> 3) * 1024;
    const uint64_t dq0 = mkdesc((sl + qoff) >> 4, 2048, 128, 0), dq1 = mkdesc((sl + qoff + 4096) >> 4, SM_ZERO - 4096 - qoff, 128, 0);
    uint64_t dk0 = mkdesc(k16, 2048, 128, 0), dk1 = mkdesc(k16 + 256, 2048, 128, 0), dv[8];
#pragma unroll
    for (int i = 0; i < 8; i++) dv[i] = mkdesc(k16 + ((SLICE + i * 768) >> 4), 384, 128, 0);
#pragma unroll
    for (int i = 0; i < 6; i++) oh[i] = 0;
    fence_u<6>(oh);
    const uint32_t inc = j0 < 8 ? (KVB >> 4) : -(KVB >> 4);
#pragma unroll 1
    for (; j0 <= jj; j0++)
#pragma unroll
      for (int u = 0; u < 2; u++) {
        mbar_wait_u(bar, 0); bar += 8;
        wg_fence();
        mma_qk_first(s, dq0, dk0); mma_qk_acc(s, dq1, dk1);
        wg_commit();
        dk0 = addlo_r(dk0, inc); dk1 = addlo_r(dk1, inc);
        wg_wait<0>();
        fence_u<32>(s);
        if (u == 0 && elect_one()) mbar_arrive(bar + (B_P - B_KV - 8));
#pragma unroll
        for (int hf = 0; hf < 2; hf++) {
#pragma unroll
          for (int i = hf * 8; i < hf * 8 + 8; i++) {
            if ((PMASK >> i) & 1) { p[2 * i] = exp_poly(s[2 * i], zero); p[2 * i + 1] = exp_poly(s[2 * i + 1], zero); }
            else { p[2 * i] = exp_mufu(s[2 * i]); p[2 * i + 1] = exp_mufu(s[2 * i + 1]); }
          }
          wg_fence();
#pragma unroll
          for (int i = hf * 4; i < hf * 4 + 4; i++) mma_pv(oh, p + 4 * i, dv[i]);
        }
        wg_commit();
#pragma unroll
        for (int i = 0; i < 8; i++) dv[i] = addlo_r(dv[i], inc);
      }
    wg_wait<0>();
    fence_u<6>(oh);
#pragma unroll
    for (int i = 0; i < 6; i++) { const float2 v = __half22float2(*(__half2*)&oh[i]); o[2 * i] += v.x; o[2 * i + 1] += v.y; }
    const int tid = fresh_tid(), bid = fresh_bid(), lane = tid & 31, g = lane >> 2, t = lane & 3;
    const int wg = __shfl_sync(~0u, tid >> 7, 0), wp = __shfl_sync(~0u, (tid >> 5) & 3, 0);
    const int h = bid >> 2, part = bid & 3, odd = h & 1, rloc = wg * 128 + wp * 16 + g;
    const float* gate = (const float*)(sm + SM_GATE) + rloc;
    const int src = (lane & ~3) | (odd ? 0 : 2);
    if ((jj & 7) == 7) {
      const float l0 = __shfl_sync(~0u, o[8], src), l1 = __shfl_sync(~0u, o[10], src);
      float chk = 0.f;
#pragma unroll
      for (int i = 0; i < 12; i++) chk += fabsf(o[i]);
      volatile uint32_t* flag = (volatile uint32_t*)(sm + SM_FLAG) + wg * 8 + (jj >> 3) * 4 + wp;
      const bool ok = *flag == 0 && l0 >= 32.f && l1 >= 32.f && chk < 1e30f;
      if (!__all_sync(~0u, ok)) { if (lane == 0) *flag = 1; }
      else {
        const float r0 = __fdividef(1.f - gate[(jj >> 3) * 64], l0), r1 = __fdividef(1.f - gate[(jj >> 3) * 64 + 8], l1);
        uint32_t v[6];
#pragma unroll
        for (int c = 0; c < 3; c++) { v[2 * c] = pack_b(o[4 * c] * r0, o[4 * c + 1] * r0); v[2 * c + 1] = pack_b(o[4 * c + 2] * r1, o[4 * c + 3] * r1); }
        store_o(v, 80, h, part * 512 + rloc + (jj >> 3) * 64, t);
      }
#pragma unroll
      for (int i = 0; i < 12; i++) o[i] = 0.f;
    } else {
      mbar_wait(sb + B_AQ, 0);
      const uint32_t kvi = (sl + SM_KVI) >> 4, img = (sl + SM_AQ + wg * SLICE) >> 4;
      mbar_wait(sb + B_KD, 0);
#pragma unroll 1
      for (int tl = 0; tl < 2; tl++) {
        float n[24];
        uint32_t e[12], v[6];
        float d[12];
        wg_fence();
        phi_logits(d, img + 64 * tl, (sl + SM_WPHI) >> 4);
        wg_commit();
        wg_wait<0>();
        phi_exp(e, d, t, zero);
        wg_fence();
        mma_b48_rs0(n, e, mkdesc(kvi, 768, 128, 0));
        mma_b48_rs(n, e + 4, mkdesc(kvi + 96, 768, 128, 0));
        mma_b48_rs(n, e + 8, mkdesc(kvi + 144, 768, 128, 0));
        wg_commit();
        wg_wait<0>();
        phi_out(v, n, gate + tl * 64, src);
        store_o(v, 0, h, part * 512 + rloc + tl * 64, t);
      }
      __syncwarp();
      if (lane == 0) mbar_arrive(sb + B_QD);
    }
    __syncwarp();
  }
  {
    const int tid = fresh_tid(), bid = fresh_bid(), lane = tid & 31;
    const int wg = __shfl_sync(~0u, tid >> 7, 0), wp = __shfl_sync(~0u, (tid >> 5) & 3, 0);
    if (wg >= 2) {
      bar_sync(8, 512);
      if (wg == 2 && tid < 264) mbar_arrive_cluster(sb + B_OE + 48 + (tid & 2) * 4, tid & 1);
      if (__any_sync(~0u, ((const uint32_t*)(sm + SM_FLAG))[lane] != 0)) attn_fallback((const uint32_t*)(sm + SM_FLAG), bid >> 2, bid & 3, P.x, P.wB);
      if (tid == 384) signal(C_OB + bid * 8);
    } else {
      bar_arrive(8, 512);
    }
    if (wg < 2) {
      float acc[40];
#pragma unroll 1
      for (int it = 0; it < 20; it++) {
        const int s = it & 7;
        bool rel = it > 0 && it <= 12;
        if (!mbar_test_wg(sb + B_OF + 8 * s, (it >> 3) & 1, 4 + wg)) {
          wg_wait<0>();
          if (rel && (tid & 127) < 2) mbar_arrive_cluster(sb + B_OE + 8 * ((it - 1) & 7), tid & 1);
          rel = false;
          mbar_wait(sb + B_OF + 8 * s, (it >> 3) & 1);
        }
        const uint32_t aa = (sl + o_slot(s) + wg * 1024) >> 4, wa = (sl + o_slot(s) + O_AB) >> 4;
        wg_fence();
#pragma unroll
        for (int k = 0; k < 4; k++) mma_n80(acc, mkdesc(aa + 256 * k, 2048, 128, 0), mkdesc(wa + 160 * k, 1280, 128, 0), (it | k) != 0);
        wg_commit();
        wg_wait<1>();
        if (rel && (tid & 127) < 2) mbar_arrive_cluster(sb + B_OE + 8 * ((it - 1) & 7), tid & 1);
      }
      wg_wait<0>();
      fence_f<40>(acc);
      const uint32_t stg = sb + o_slot(6) + wg * 10240;
      const uint32_t ad = stg + (wp * 16 + ((lane >> 3) & 1) * 8 + (lane & 7)) * 160 + (lane >> 4) * 16;
      bar_sync(1, 256);
#pragma unroll
      for (int i = 0; i < 5; i++)
        stsm4(ad + i * 32, pack_b(acc[8 * i], acc[8 * i + 1]), pack_b(acc[8 * i + 2], acc[8 * i + 3]), pack_b(acc[8 * i + 4], acc[8 * i + 5]), pack_b(acc[8 * i + 6], acc[8 * i + 7]));
      fence_async();
      bar_sync(4 + wg, 128);
      if ((tid & 127) == 0) {
        tma2d_store(&P.tmOut, stg, (bid & 7) * 80, (bid >> 3) * 128 + wg * 64);
        bulk_commit();
        asm volatile("cp.async.bulk.wait_group.read 0;" ::: "memory");
      }
    }
  }
}

typedef CUresult (*EncodeFn)(CUtensorMap*, CUtensorMapDataType, cuuint32_t, void*, const cuuint64_t*, const cuuint64_t*, const cuuint32_t*,
                             const cuuint32_t*, CUtensorMapInterleave, CUtensorMapSwizzle, CUtensorMapL2promotion, CUtensorMapFloatOOBfill);

void encode(EncodeFn fn, CUtensorMap* m, const void* p, int rank, const cuuint64_t* dims, const cuuint64_t* strides, const cuuint32_t* box, CUtensorMapSwizzle swz) {
  const cuuint32_t es[3] = {1, 1, 1};
  CUresult r = fn(m, CU_TENSOR_MAP_DATA_TYPE_BFLOAT16, rank, const_cast<void*>(p), dims, strides, box, es, CU_TENSOR_MAP_INTERLEAVE_NONE, swz,
                  CU_TENSOR_MAP_L2_PROMOTION_L2_256B, CU_TENSOR_MAP_FLOAT_OOB_FILL_NONE);
  if (r != CUDA_SUCCESS) fprintf(stderr, "tensor map encode failed: %d\n", (int)r);
}

}

extern "C" void kernel_launch(void* const* d_in, const int* in_sizes, int n_in, void* d_out, int out_size) {
  (void)in_sizes; (void)n_in; (void)out_size;
  static EncodeFn fn = nullptr;
  if (!fn) {
    void* p = nullptr;
    cudaDriverEntryPointQueryResult qr;
    cudaGetDriverEntryPoint("cuTensorMapEncodeTiled", &p, cudaEnableDefault, &qr);
    fn = (EncodeFn)p;
    cudaFuncSetAttribute(fused_kernel, cudaFuncAttributeMaxDynamicSharedMemorySize, SM_TOTAL);
  }
  Params P;
  P.x = (const __nv_bfloat16*)d_in[0];
  P.w_phi = (const __nv_bfloat16*)d_in[2];
  P.wB = (const __nv_bfloat16*)d_in[5];
  P.gate_w = (const __nv_bfloat16*)d_in[7];
  P.woA = (const __nv_bfloat16*)d_in[3];
  P.woB = (const __nv_bfloat16*)d_in[6];
  {
    const cuuint64_t d[2] = {640, 2048}, st[1] = {1280};
    const cuuint32_t box[2] = {64, 128}, obox[2] = {80, 64};
    encode(fn, &P.tmX, d_in[0], 2, d, st, box, CU_TENSOR_MAP_SWIZZLE_128B);
    encode(fn, &P.tmOut, d_out, 2, d, st, obox, CU_TENSOR_MAP_SWIZZLE_NONE);
  }
  {
    const cuuint64_t d[2] = {1920, 640}, st[1] = {3840};
    const cuuint32_t box[2] = {64, 32};
    encode(fn, &P.tmWA, d_in[1], 2, d, st, box, CU_TENSOR_MAP_SWIZZLE_128B);
    encode(fn, &P.tmWB, d_in[5], 2, d, st, box, CU_TENSOR_MAP_SWIZZLE_128B);
  }
  fused_kernel<<<128, 640, SM_TOTAL, cudaStreamPerThread>>>(P);
}
```

```cpp
#include <cuda_runtime.h>
#include <cuda_bf16.h>
#include <cuda_fp16.h>
#include <cuda.h>
#include <stdint.h>
#include <stdio.h>


namespace {

constexpr int S_ = 2048, D_ = 640, H_ = 32;
constexpr int SLICE = 6144;
constexpr int KVB = 2 * SLICE;
constexpr uint32_t PMASK = 0xADADu;
constexpr float QSCALE = 0.32259642f;

__device__ __align__(1024) uint8_t g_qB[H_ * 16 * SLICE];
__device__ __align__(1024) uint8_t g_kvB[H_ * 16 * KVB];
__device__ __align__(1024) uint8_t g_A[3 * H_ * 16 * SLICE];
__device__ __align__(1024) uint8_t g_o[16 * 160 * 2048];
__device__ __align__(1024) uint8_t g_wo[8 * 20 * 10240];
__device__ __align__(128) float g_stat[H_ * 32];
__device__ __align__(16) float g_gate[S_];
__device__ __align__(16) float g_kvs[H_ * 40 * 24];
__device__ __align__(16) __nv_bfloat16 g_fb[H_ * S_ * 40];
constexpr int C_B = 0, C_EXIT = 64, C_OA = 96, C_KV = 224, C_A = C_KV + 32 * 32, C_OB = C_A + 4, C_N = C_A + 128 * 8;
__device__ __align__(128) unsigned int g_cnt[C_N];

__device__ __forceinline__ uint32_t smem_u32(const void* p) { return (uint32_t)__cvta_generic_to_shared(p); }
__device__ __forceinline__ uint64_t mkdesc(uint32_t a16, uint32_t lbo, uint32_t sbo, uint32_t swz) {
  uint32_t lo = a16 + ((lbo >> 4) << 16);
  uint32_t hi = (sbo >> 4) | (swz << 30);
  return ((uint64_t)hi << 32) | lo;
}
template <int INC> __device__ __forceinline__ uint64_t addlo(uint64_t d) {
  asm volatile("{.reg .b32 lo, hi; mov.b64 {lo,hi}, %0; add.u32 lo, lo, %1; mov.b64 %0, {lo,hi};}" : "+l"(d) : "n"(INC));
  return d;
}
__device__ __forceinline__ uint64_t addlo_r(uint64_t d, uint32_t inc) {
  asm volatile("{.reg .b32 lo, hi; mov.b64 {lo,hi}, %0; add.u32 lo, lo, %1; mov.b64 %0, {lo,hi};}" : "+l"(d) : "r"(inc));
  return d;
}
__device__ __forceinline__ void wg_fence() { asm volatile("wgmma.fence.sync.aligned;" ::: "memory"); }
__device__ __forceinline__ void wg_commit() { asm volatile("wgmma.commit_group.sync.aligned;" ::: "memory"); }
template <int N> __device__ __forceinline__ void wg_wait() { asm volatile("wgmma.wait_group.sync.aligned %0;" ::"n"(N) : "memory"); }
template <int N> __device__ __forceinline__ void fence_f(float* r) {
#pragma unroll
  for (int i = 0; i < N; i++) asm volatile("" : "+f"(r[i])::"memory");
}
template <int N> __device__ __forceinline__ void fence_u(uint32_t* r) {
#pragma unroll
  for (int i = 0; i < N; i++) asm volatile("" : "+r"(r[i])::"memory");
}
__device__ __forceinline__ void mbar_init(uint32_t bar, uint32_t cnt) { asm volatile("mbarrier.init.shared::cta.b64 [%0], %1;" ::"r"(bar), "r"(cnt) : "memory"); }
__device__ __forceinline__ void mbar_expect_tx(uint32_t bar, uint32_t bytes) { asm volatile("mbarrier.arrive.expect_tx.shared::cta.b64 _, [%0], %1;" ::"r"(bar), "r"(bytes) : "memory"); }
__device__ __forceinline__ void mbar_wait(uint32_t bar, uint32_t parity) {
  asm volatile(
      "{\n.reg .pred p;\n.reg .u32 n;\nmov.u32 n, 0;\n"
      "W: mbarrier.try_wait.parity.shared::cta.b64 p, [%0], %1;\n@p bra D;\n"
      "add.u32 n, n, 1;\nsetp.lt.u32 p, n, 0x1000000;\n@p bra W;\ntrap;\nD:\n}" ::"r"(bar), "r"(parity) : "memory");
}
__device__ __forceinline__ bool mbar_test_wg(uint32_t bar, uint32_t parity, int id) {
  uint32_t r;
  asm volatile("{.reg .pred p, q; mbarrier.test_wait.parity.shared::cta.b64 p, [%1], %2; bar.red.and.pred q, %3, 128, p; selp.u32 %0, 1, 0, q;}"
               : "=r"(r) : "r"(bar), "r"(parity), "r"(id) : "memory");
  return r != 0;
}
__device__ __forceinline__ void mbar_wait_z(uint32_t bar, uint32_t parity) {
  asm volatile(
      "{\n.reg .pred p;\n.reg .u32 n;\nmov.u32 n, 0;\n"
      "W: mbarrier.try_wait.parity.shared::cta.b64 p, [%0], %1, 20000;\n@p bra D;\n"
      "add.u32 n, n, 1;\nsetp.lt.u32 p, n, 0x100000;\n@p bra W;\ntrap;\nD:\n}" ::"r"(bar), "r"(parity) : "memory");
}
__device__ __forceinline__ void mbar_wait_u(uint32_t bar, uint32_t parity) {
  asm volatile("{\n.reg .pred p;\nW: mbarrier.try_wait.parity.shared::cta.b64 p, [%0], %1;\n@p bra D;\nbra W;\nD:\n}" ::"r"(bar), "r"(parity) : "memory");
}
__device__ __forceinline__ void mbar_arrive_cluster(uint32_t bar, uint32_t cta) {
  asm volatile("{.reg .b32 r; mapa.shared::cluster.u32 r, %0, %1; mbarrier.arrive.shared::cluster.b64 _, [r];}" ::"r"(bar), "r"(cta) : "memory");
}
__device__ __forceinline__ void bulk_g2s(uint32_t dst, const void* src, uint32_t bytes, uint32_t bar) {
  asm volatile("cp.async.bulk.shared::cluster.global.mbarrier::complete_tx::bytes [%0], [%1], %2, [%3];" ::"r"(dst), "l"(src), "r"(bytes), "r"(bar) : "memory");
}
__device__ __forceinline__ void bulk_g2s_mc(uint32_t dst, const void* src, uint32_t bytes, uint32_t bar, uint16_t mask) {
  asm volatile("cp.async.bulk.shared::cluster.global.mbarrier::complete_tx::bytes.multicast::cluster [%0], [%1], %2, [%3], %4;" ::"r"(dst), "l"(src), "r"(bytes), "r"(bar), "h"(mask) : "memory");
}
__device__ __forceinline__ void bulk_s2g(void* dst, uint32_t src, uint32_t bytes) {
  asm volatile("cp.async.bulk.global.shared::cta.bulk_group [%0], [%1], %2;" ::"l"(dst), "r"(src), "r"(bytes) : "memory");
}
__device__ __forceinline__ void tma2d(uint32_t dst, const CUtensorMap* m, int c0, int c1, uint32_t bar) {
  asm volatile("cp.async.bulk.tensor.2d.shared::cluster.global.mbarrier::complete_tx::bytes [%0], [%1, {%3, %4}], [%2];" ::"r"(dst), "l"(m), "r"(bar), "r"(c0), "r"(c1) : "memory");
}
__device__ __forceinline__ void tma2d_mc(uint32_t dst, const CUtensorMap* m, int c0, int c1, uint32_t bar, uint16_t mask) {
  asm volatile("cp.async.bulk.tensor.2d.shared::cluster.global.mbarrier::complete_tx::bytes.multicast::cluster [%0], [%1, {%3, %4}], [%2], %5;" ::"r"(dst), "l"(m), "r"(bar), "r"(c0), "r"(c1), "h"(mask) : "memory");
}
__device__ __forceinline__ void tma2d_store(const CUtensorMap* m, uint32_t src, int c0, int c1) {
  asm volatile("cp.async.bulk.tensor.2d.global.shared::cta.bulk_group [%0, {%2, %3}], [%1];" ::"l"(m), "r"(src), "r"(c0), "r"(c1) : "memory");
}
__device__ __forceinline__ void bulk_commit() { asm volatile("cp.async.bulk.commit_group;" ::: "memory"); }
__device__ __forceinline__ void bulk_wait_all() { asm volatile("cp.async.bulk.wait_group 0;" ::: "memory"); }
__device__ __forceinline__ void fence_async() { asm volatile("fence.proxy.async.shared::cta;" ::: "memory"); }
__device__ __forceinline__ void bar_sync(int id, int n) { asm volatile("bar.sync %0, %1;" ::"r"(id), "r"(n) : "memory"); }
__device__ __forceinline__ void bar_arrive(int id, int n) { asm volatile("bar.arrive %0, %1;" ::"r"(id), "r"(n) : "memory"); }
__device__ __forceinline__ void mbar_arrive(uint32_t bar) { asm volatile("mbarrier.arrive.shared::cta.b64 _, [%0];" ::"r"(bar) : "memory"); }
__device__ __forceinline__ void fence_async_g() { asm volatile("fence.proxy.async.global;" ::: "memory"); }
__device__ __forceinline__ void signal(int c) { asm volatile("red.release.gpu.global.add.u32 [%0], 1;" ::"l"(g_cnt + c) : "memory"); }
__device__ __forceinline__ void await(int c, uint32_t target) {
  asm volatile(
      "{\n.reg .pred p;\n.reg .u32 n, v;\nmov.u32 n, 0;\n"
      "W: ld.acquire.gpu.global.u32 v, [%0];\nsetp.ge.u32 p, v, %1;\n@p bra D;\n"
      "nanosleep.u32 64;\nadd.u32 n, n, 1;\nsetp.lt.u32 p, n, 0x400000;\n@p bra W;\ntrap;\nD:\n}" ::"l"(g_cnt + c), "r"(target) : "memory");
}
__device__ __forceinline__ void await_all(int c, uint32_t target) {
  asm volatile(
      "{\n.reg .pred p;\n.reg .u32 n, v;\nmov.u32 n, 0;\n"
      "W: ld.acquire.gpu.global.u32 v, [%0];\nsetp.ge.u32 p, v, %1;\nvote.sync.all.pred p, p, 0xffffffff;\n@p bra.uni D;\n"
      "nanosleep.u32 64;\nadd.u32 n, n, 1;\nsetp.lt.u32 p, n, 0x400000;\n@p bra.uni W;\ntrap;\nD:\n}" ::"l"(g_cnt + c), "r"(target) : "memory");
}
__device__ __forceinline__ uint32_t await_mask(int c, uint32_t need) {
  uint32_t m;
  asm volatile(
      "{\n.reg .pred p;\n.reg .u32 n, v;\nmov.u32 n, 0;\n"
      "W: ld.acquire.gpu.global.u32 v, [%1];\nsetp.ne.u32 p, v, 0;\nvote.sync.ballot.b32 %0, p, 0xffffffff;\n"
      "and.b32 v, %0, %2;\nsetp.eq.u32 p, v, %2;\n@p bra.uni D;\n"
      "add.u32 n, n, 1;\nsetp.lt.u32 p, n, 0x400000;\n@p bra.uni W;\ntrap;\nD:\n}" : "=r"(m) : "l"(g_cnt + c), "r"(need) : "memory");
  return m;
}
__device__ __forceinline__ bool elect_one() {
  uint32_t p;
  asm volatile("{.reg .pred p; elect.sync _|p, 0xffffffff; selp.u32 %0, 1, 0, p;}" : "=r"(p));
  return p != 0;
}
__device__ __forceinline__ int fresh_tid() { int v; asm volatile("mov.u32 %0, %%tid.x;" : "=r"(v)); return v < 128 ? v + 512 : v - 128; }
__device__ __forceinline__ int fresh_bid() { int v; asm volatile("mov.u32 %0, %%ctaid.x;" : "=r"(v)); return v; }
__device__ __forceinline__ void stsm2(uint32_t addr, uint32_t a, uint32_t b) {
  asm volatile("stmatrix.sync.aligned.m8n8.x2.shared.b16 [%0], {%1,%2};" ::"r"(addr), "r"(a), "r"(b) : "memory");
}
__device__ __forceinline__ uint4 lds128(uint32_t a) { uint4 v; asm volatile("ld.shared.v4.u32 {%0,%1,%2,%3}, [%4];" : "=r"(v.x), "=r"(v.y), "=r"(v.z), "=r"(v.w) : "r"(a) : "memory"); return v; }
__device__ __forceinline__ void stsm4(uint32_t addr, uint32_t a, uint32_t b, uint32_t c, uint32_t d) {
  asm volatile("stmatrix.sync.aligned.m8n8.x4.shared.b16 [%0], {%1,%2,%3,%4};" ::"r"(addr), "r"(a), "r"(b), "r"(c), "r"(d) : "memory");
}
__device__ __forceinline__ uint32_t pack_h(float lo, float hi) { uint32_t r; asm("cvt.rn.f16x2.f32 %0, %1, %2;" : "=r"(r) : "f"(hi), "f"(lo)); return r; }
__device__ __forceinline__ uint32_t pack_b(float lo, float hi) { uint32_t r; asm("cvt.rn.bf16x2.f32 %0, %1, %2;" : "=r"(r) : "f"(hi), "f"(lo)); return r; }
__device__ __forceinline__ float ex2f(float x) { float r; asm("ex2.approx.ftz.f32 %0, %1;" : "=f"(r) : "f"(x)); return r; }
__device__ __forceinline__ float bf_lo(uint32_t u) { return __uint_as_float(u << 16); }
__device__ __forceinline__ float bf_hi(uint32_t u) { return __uint_as_float(u & 0xffff0000u); }

#define F4(o) "+f"(d[o + 0]), "+f"(d[o + 1]), "+f"(d[o + 2]), "+f"(d[o + 3])
#define F8(o) F4(o), F4(o + 4)
#define F40(o) F8(o), F8(o + 8), F8(o + 16), F8(o + 24), F8(o + 32)
#define RU8(o) "+r"(d[o + 0]), "+r"(d[o + 1]), "+r"(d[o + 2]), "+r"(d[o + 3]), "+r"(d[o + 4]), "+r"(d[o + 5]), "+r"(d[o + 6]), "+r"(d[o + 7])
#define WU8(o) "=r"(d[o + 0]), "=r"(d[o + 1]), "=r"(d[o + 2]), "=r"(d[o + 3]), "=r"(d[o + 4]), "=r"(d[o + 5]), "=r"(d[o + 6]), "=r"(d[o + 7])
#define A4 "r"(a[0]), "r"(a[1]), "r"(a[2]), "r"(a[3])

__device__ __forceinline__ void mma_n128(float* d, uint64_t a, uint64_t b, int acc) {
  asm volatile(
      "{.reg .pred p; setp.ne.b32 p, %66, 0;\n"
      "wgmma.mma_async.sync.aligned.m64n128k16.f32.bf16.bf16 {"
      "%0,%1,%2,%3,%4,%5,%6,%7,%8,%9,%10,%11,%12,%13,%14,%15,%16,%17,%18,%19,%20,%21,%22,%23,"
      "%24,%25,%26,%27,%28,%29,%30,%31,%32,%33,%34,%35,%36,%37,%38,%39,%40,%41,%42,%43,%44,%45,%46,%47,"
      "%48,%49,%50,%51,%52,%53,%54,%55,%56,%57,%58,%59,%60,%61,%62,%63"
      "}, %64, %65, p, 1, 1, 0, 1;}"
      : F40(0), F8(40), F8(48), F8(56)
      : "l"(a), "l"(b), "r"(acc));
}
__device__ __forceinline__ void mma_n112(float* d, uint64_t a, uint64_t b, int acc) {
  asm volatile(
      "{.reg .pred p; setp.ne.b32 p, %58, 0;\n"
      "wgmma.mma_async.sync.aligned.m64n112k16.f32.bf16.bf16 {"
      "%0,%1,%2,%3,%4,%5,%6,%7,%8,%9,%10,%11,%12,%13,%14,%15,%16,%17,%18,%19,%20,%21,%22,%23,"
      "%24,%25,%26,%27,%28,%29,%30,%31,%32,%33,%34,%35,%36,%37,%38,%39,%40,%41,%42,%43,%44,%45,%46,%47,"
      "%48,%49,%50,%51,%52,%53,%54,%55"
      "}, %56, %57, p, 1, 1, 0, 1;}"
      : F40(0), F8(40), F8(48)
      : "l"(a), "l"(b), "r"(acc));
}
__device__ __forceinline__ void mma_n80(float* d, uint64_t a, uint64_t b, int acc) {
  asm volatile(
      "{.reg .pred p; setp.ne.b32 p, %42, 0;\n"
      "wgmma.mma_async.sync.aligned.m64n80k16.f32.bf16.bf16 {"
      "%0,%1,%2,%3,%4,%5,%6,%7,%8,%9,%10,%11,%12,%13,%14,%15,%16,%17,%18,%19,%20,%21,%22,%23,%24,%25,%26,%27,%28,%29,"
      "%30,%31,%32,%33,%34,%35,%36,%37,%38,%39}, %40, %41, p, 1, 1, 0, 1;}"
      : F40(0)
      : "l"(a), "l"(b), "r"(acc));
}
__device__ __forceinline__ void mma_qk_first(uint32_t* d, uint64_t a, uint64_t b) {
  asm volatile(
      "wgmma.mma_async.sync.aligned.m64n128k16.f16.f16.f16 {%0,%1,%2,%3,%4,%5,%6,%7,%8,%9,%10,%11,%12,%13,%14,%15,%16,%17,%18,%19,%20,%21,%22,%23,%24,%25,%26,%27,%28,%29,%30,%31}, %32, %33, 0, 1, 1, 0, 0;"
      : WU8(0), WU8(8), WU8(16), WU8(24)
      : "l"(a), "l"(b));
}
__device__ __forceinline__ void mma_qk_acc(uint32_t* d, uint64_t a, uint64_t b) {
  asm volatile(
      "wgmma.mma_async.sync.aligned.m64n128k16.f16.f16.f16 {%0,%1,%2,%3,%4,%5,%6,%7,%8,%9,%10,%11,%12,%13,%14,%15,%16,%17,%18,%19,%20,%21,%22,%23,%24,%25,%26,%27,%28,%29,%30,%31}, %32, %33, 1, 1, 1, 0, 0;"
      : RU8(0), RU8(8), RU8(16), RU8(24)
      : "l"(a), "l"(b));
}
__device__ __forceinline__ void mma_pv(uint32_t* d, const uint32_t* a, uint64_t b) {
  asm volatile("wgmma.mma_async.sync.aligned.m64n24k16.f16.f16.f16 {%0,%1,%2,%3,%4,%5}, {%6,%7,%8,%9}, %10, 1, 1, 1, 1;"
               : "+r"(d[0]), "+r"(d[1]), "+r"(d[2]), "+r"(d[3]), "+r"(d[4]), "+r"(d[5])
               : A4, "l"(b));
}
#define W4(o) "=f"(d[o + 0]), "=f"(d[o + 1]), "=f"(d[o + 2]), "=f"(d[o + 3])
__device__ __forceinline__ void mma_b48_rs0(float* d, const uint32_t* a, uint64_t b) {
  asm volatile("wgmma.mma_async.sync.aligned.m64n48k16.f32.bf16.bf16 {%0,%1,%2,%3,%4,%5,%6,%7,%8,%9,%10,%11,%12,%13,%14,%15,%16,%17,%18,%19,%20,%21,%22,%23}, {%24,%25,%26,%27}, %28, 0, 1, 1, 0;"
               : W4(0), W4(4), W4(8), W4(12), W4(16), W4(20)
               : A4, "l"(b));
}
__device__ __forceinline__ void mma_b48_rs(float* d, const uint32_t* a, uint64_t b) {
  asm volatile("wgmma.mma_async.sync.aligned.m64n48k16.f32.bf16.bf16 {%0,%1,%2,%3,%4,%5,%6,%7,%8,%9,%10,%11,%12,%13,%14,%15,%16,%17,%18,%19,%20,%21,%22,%23}, {%24,%25,%26,%27}, %28, 1, 1, 1, 0;"
               : F8(0), F8(8), F8(16)
               : A4, "l"(b));
}
__device__ __forceinline__ void mma_b8_rs0(float* d, const uint32_t* a, uint64_t b) {
  asm volatile("wgmma.mma_async.sync.aligned.m64n8k16.f32.bf16.bf16 {%0,%1,%2,%3}, {%4,%5,%6,%7}, %8, 0, 1, 1, 0;" : W4(0) : A4, "l"(b));
}
__device__ __forceinline__ void mma_b8_rs(float* d, const uint32_t* a, uint64_t b) {
  asm volatile("wgmma.mma_async.sync.aligned.m64n8k16.f32.bf16.bf16 {%0,%1,%2,%3}, {%4,%5,%6,%7}, %8, 1, 1, 1, 0;" : F4(0) : A4, "l"(b));
}
__device__ __forceinline__ uint32_t mul_b2(uint32_t a, uint32_t b) { uint32_t r; asm("mul.rn.bf16x2 %0, %1, %2;" : "=r"(r) : "r"(a), "r"(b)); return r; }
__device__ __forceinline__ void mma_b24_ss0(float* d, uint64_t a, uint64_t b) {
  asm volatile("wgmma.mma_async.sync.aligned.m64n24k16.f32.bf16.bf16 {%0,%1,%2,%3,%4,%5,%6,%7,%8,%9,%10,%11}, %12, %13, 0, 1, 1, 0, 0;"
               : W4(0), W4(4), W4(8)
               : "l"(a), "l"(b));
}
__device__ __forceinline__ void mma_b24_ss(float* d, uint64_t a, uint64_t b) {
  asm volatile("wgmma.mma_async.sync.aligned.m64n24k16.f32.bf16.bf16 {%0,%1,%2,%3,%4,%5,%6,%7,%8,%9,%10,%11}, %12, %13, 1, 1, 1, 0, 0;"
               : F4(0), F4(4), F4(8)
               : "l"(a), "l"(b));
}
__device__ __forceinline__ void mma_b24_tt0(float* d, uint64_t a, uint64_t b) {
  asm volatile("wgmma.mma_async.sync.aligned.m64n24k16.f32.bf16.bf16 {%0,%1,%2,%3,%4,%5,%6,%7,%8,%9,%10,%11}, %12, %13, 0, 1, 1, 1, 1;"
               : W4(0), W4(4), W4(8)
               : "l"(a), "l"(b));
}
__device__ __forceinline__ void mma_b24_tt(float* d, uint64_t a, uint64_t b) {
  asm volatile("wgmma.mma_async.sync.aligned.m64n24k16.f32.bf16.bf16 {%0,%1,%2,%3,%4,%5,%6,%7,%8,%9,%10,%11}, %12, %13, 1, 1, 1, 1, 1;"
               : F4(0), F4(4), F4(8)
               : "l"(a), "l"(b));
}

constexpr int G_XB = 16384, G_WB = 16384, G_PB = G_XB + 2 * G_WB;
constexpr int SM_STG = 3 * G_PB;
constexpr int SM_Q = 0, KV0 = 4 * SLICE;
constexpr int SM_PHI = KV0 + 4 * KVB;
constexpr int SM_AQ = KV0 + 14 * KVB;
constexpr int SM_MISC = SM_STG + 12 * SLICE;
constexpr int B_FULL = SM_MISC, B_EMPTY = B_FULL + 48, B_KV = B_EMPTY + 48, B_BD = B_KV + 256, B_QR = B_BD + 8, B_AV = B_QR + 8,
              B_AQ = B_AV + 8, B_KD = B_AQ + 8, B_QD = B_KD + 8, B_OF = B_QD + 8, B_OE = B_OF + 64, B_P = B_OE + 64;
constexpr int SM_FLAG = SM_MISC + 896;
constexpr int SM_WPHI = SM_MISC + 1024;
constexpr int SM_RED = SM_WPHI + 1536;
constexpr int SM_GATE = SM_RED + 256;
constexpr int SM_IND = SM_GATE + 2048;
constexpr int SM_KVI = SM_IND + 640;
constexpr int SM_ZERO = SM_KVI + 3840;
constexpr int SM_TOTAL = SM_ZERO + 1024;
constexpr int O_AB = 16384, O_WB = 10240, O_STB = O_AB + O_WB;
__host__ __device__ constexpr int o_slot(int i) { return SM_MISC - (i + 1) * O_STB; }

template <bool BR_B>
__device__ __forceinline__ void g_epilogue(float* acc, uint32_t stg, int ct, int w, int wp, int lane) {
  const int t = lane & 3, hf = (lane >> 3) & 1, csel = lane >> 4, r = lane & 7;
  const int Rw = w * 64 + wp * 16;
  const uint32_t offK = Rw * 16 + hf * 128 + r * 16, offV = (Rw / 8 + hf) * 384 + r * 16;
  const bool p0 = (PMASK >> (Rw / 8)) & 1, p1 = (PMASK >> (Rw / 8 + 1)) & 1;
  const bool lo = t < 2, ev = !(t & 1);
#pragma unroll
  for (int j = 0; j < 6; j++) {
    const int type = (ct * 12 + 2 * j) >> 5;
    float* a = acc + 20 * j;
    uint32_t aug0, aug1, q[10];
    if (BR_B) {
      const float s0 = type == 0 ? QSCALE : (type == 1 && p0) ? 0.001953125f : 1.f;
      const float s1 = type == 0 ? QSCALE : (type == 1 && p1) ? 0.001953125f : 1.f;
      aug0 = (type == 0 || !ev) ? 0u : (type == 1 && p0) ? 0x18001800u : 0x00003C00u;
      aug1 = (type == 0 || !ev) ? 0u : (type == 1 && p1) ? 0x18001800u : 0x00003C00u;
#pragma unroll
      for (int i = 0; i < 5; i++) { q[2 * i] = pack_h(a[4 * i] * s0, a[4 * i + 1] * s0); q[2 * i + 1] = pack_h(a[4 * i + 2] * s1, a[4 * i + 3] * s1); }
    } else {
      aug0 = aug1 = (type == 2 && ev) ? 0x00003F80u : 0u;
#pragma unroll
      for (int i = 0; i < 10; i++) q[i] = pack_b(a[2 * i], a[2 * i + 1]);
    }
    const uint32_t base = stg + 2 * j * SLICE + (type == 2 ? offV : offK);
    const uint32_t cs = type == 2 ? 128 : 2048;
    stsm4(base + csel * cs, q[0], q[1], q[2], q[3]);
    stsm4(base + 2 * cs + csel * SLICE, lo ? q[4] : aug0, lo ? q[5] : aug1, lo ? aug0 : q[4], lo ? aug1 : q[5]);
    stsm4(base + SLICE + csel * cs, q[6], q[7], q[8], q[9]);
  }
}

__device__ __forceinline__ uint32_t exp_mufu(uint32_t s) { uint32_t r; asm("ex2.approx.f16x2 %0, %1;" : "=r"(r) : "r"(s)); return r; }
__device__ __forceinline__ uint32_t hfma(uint32_t a, uint32_t b, uint32_t c) { uint32_t r; asm("fma.rn.f16x2 %0, %1, %2, %3;" : "=r"(r) : "r"(a), "r"(b), "r"(c)); return r; }
__device__ __forceinline__ uint32_t hfma_relu(uint32_t a, uint32_t b, uint32_t c) { uint32_t r; asm("fma.rn.relu.f16x2 %0, %1, %2, %3;" : "=r"(r) : "r"(a), "r"(b), "r"(c)); return r; }
#define D2(x) ((x) * 0x10001u)
__device__ __forceinline__ uint32_t exp_poly(uint32_t u, uint32_t zero) {
  uint32_t r = hfma_relu(u, D2(0x0200u), 0u);
  uint32_t f = hfma(r, D2(0xF800u), u);
  uint32_t w = hfma(f, D2(0x60fcu), D2(0x457fu));
  w = hfma(f, w, D2(0x27d8u));
  w = hfma_relu(f, w, D2(0x05a8u));
  return __funnelshift_l(zero, r, 10) + w;
}

__device__ __forceinline__ void phi_logits(float* d, uint32_t img16, uint32_t wphi16) {
  mma_b24_ss0(d, mkdesc(img16, 2048, 128, 0), mkdesc(wphi16, 384, 128, 0));
  mma_b24_ss(d, mkdesc(img16 + 128, 2048, 128, 0), mkdesc(wphi16 + 48, 384, 128, 0));
}
__device__ __forceinline__ void phi_exp(uint32_t* e, float* d, int t, uint32_t zero) {
  fence_f<12>(d);
#pragma unroll
  for (int i = 0; i < 12; i++) d[i] *= 1.4426950408889634f;
  const bool lo = t < 2;
  const uint32_t sgn = lo ? 0u : 0x80000000u;
#pragma unroll
  for (int hf = 0; hf < 2; hf++) {
    const float* x = d + 2 * hf;
    e[hf] = pack_b(ex2f(x[0]), ex2f(x[1])); e[2 + hf] = pack_b(ex2f(x[4]), ex2f(x[5]));
    e[4 + hf] = pack_b(ex2f(__uint_as_float(__float_as_uint(x[8]) ^ sgn)), ex2f(__uint_as_float(__float_as_uint(x[9]) ^ sgn)));
    e[6 + hf] = pack_b(ex2f(-x[0]), ex2f(-x[1])); e[10 + hf] = pack_b(ex2f(-x[4]), ex2f(-x[5]));
  }
  float am[3];
#pragma unroll
  for (int i = 0; i < 3; i++) am[i] = fmaxf(fmaxf(fabsf(d[4 * i]), fabsf(d[4 * i + 1])), fmaxf(fabsf(d[4 * i + 2]), fabsf(d[4 * i + 3])));
  if (!__all_sync(~0u, fmaxf(fmaxf(am[0], am[1]), am[2]) <= 40.f)) {
#pragma unroll
    for (int hf = 0; hf < 2; hf++) {
      const float* x = d + 2 * hf;
      float mx = fmaxf(fmaxf(fmaxf(x[0], x[1]), fmaxf(x[4], x[5])), fmaxf(x[8], x[9]));
      float mn = fminf(fminf(fminf(x[0], x[1]), fminf(x[4], x[5])), fminf(x[8], x[9]));
      mx = fmaxf(mx, __shfl_xor_sync(~0u, mx, 1)); mn = fminf(mn, __shfl_xor_sync(~0u, mn, 1));
      mx = fmaxf(mx, __shfl_xor_sync(~0u, mx, 2)); mn = fminf(mn, __shfl_xor_sync(~0u, mn, 2));
      e[hf] = pack_b(ex2f(x[0] - mx), ex2f(x[1] - mx)); e[2 + hf] = pack_b(ex2f(x[4] - mx), ex2f(x[5] - mx));
      e[4 + hf] = pack_b(ex2f(lo ? x[8] - mx : mn - x[8]), ex2f(lo ? x[9] - mx : mn - x[9]));
      e[6 + hf] = pack_b(ex2f(mn - x[0]), ex2f(mn - x[1])); e[10 + hf] = pack_b(ex2f(mn - x[4]), ex2f(mn - x[5]));
    }
  }
  e[8] = zero; e[9] = zero;
  fence_u<12>(e);
}

__device__ __forceinline__ void phi_out(uint32_t* v, float* d, const float* gate, int src) {
  fence_f<24>(d);
#pragma unroll
  for (int hf = 0; hf < 2; hf++) {
    const float rp = __fdividef(1.f, d[9 + 2 * hf]), rn = __fdividef(1.f, d[21 + 2 * hf]);
    const float sc = __fdividef(gate[8 * hf], fmaf(d[8 + 2 * hf], rp, fmaf(d[20 + 2 * hf], rn, 1e-6f)));
    const float a = __shfl_sync(~0u, rp * sc, src), b = __shfl_sync(~0u, rn * sc, src);
#pragma unroll
    for (int c = 0; c < 3; c++)
      v[2 * c + hf] = pack_b(fmaf(d[12 + 4 * c + 2 * hf], b, d[4 * c + 2 * hf] * a), fmaf(d[13 + 4 * c + 2 * hf], b, d[4 * c + 2 * hf + 1] * a));
  }
}

__device__ __forceinline__ void store_o(const uint32_t* v, int cbase, int h, int row, int t) {
  uint32_t* p = (uint32_t*)(g_o + ((row >> 7) * 160 + cbase + (h >> 1) * 5) * 2048 + (row & 127) * 16) + t;
  uint32_t* p0 = p + ((h & 1) ? 1536 : 0);
  p0[0] = v[0]; p0[32] = v[1]; p0[512] = v[2]; p0[544] = v[3];
  if ((t >> 1) == (h & 1)) { p[1024] = v[4]; p[1056] = v[5]; }
}

__device__ __noinline__ void attn_fallback(const uint32_t* flags, int h, int part, const __nv_bfloat16* x, const __nv_bfloat16* wB) {
  __nv_bfloat16* kv = g_fb + (size_t)h * S_ * 40;
  const int tid = fresh_tid() - 256;
  for (int i = tid; i < S_ * 40; i += 256) {
    const int tok = i / 40, c = i % 40;
    const __nv_bfloat16* xr = x + (size_t)tok * D_;
    const __nv_bfloat16* wc = wB + (c < 20 ? 640 + h * 20 + c : 1280 + h * 20 + c - 20);
    float acc = 0.f;
    for (int k = 0; k < D_; k++) acc += __bfloat162float(xr[k]) * __bfloat162float(wc[(size_t)k * 1920]);
    kv[i] = __float2bfloat16(acc);
  }
  bar_sync(12, 256);
  const int warp = tid >> 5, lane = tid & 31;
  for (int wt = warp; wt < 32; wt += 8) {
    if (!flags[wt]) continue;
    for (int rr = 0; rr < 16; rr++) {
      const int row = part * 512 + wt * 16 + rr;
      float qv = 0.f;
      if (lane < 20) {
        for (int k = 0; k < D_; k++) qv += __bfloat162float(x[(size_t)row * D_ + k]) * __bfloat162float(wB[(size_t)k * 1920 + h * 20 + lane]);
        qv = __bfloat162float(__float2bfloat16(qv));
      }
      float m = -INFINITY, l = 0.f, o[20];
#pragma unroll
      for (int d = 0; d < 20; d++) o[d] = 0.f;
      for (int j = lane; j < S_; j += 32) {
        float s = 0.f;
#pragma unroll
        for (int d = 0; d < 20; d++) s += __shfl_sync(~0u, qv, d) * __bfloat162float(kv[j * 40 + d]);
        s = __bfloat162float(__float2bfloat16(__bfloat162float(__float2bfloat16(s)) * 0.22360679775f)) * 1.4426950408889634f;
        const float mn = fmaxf(m, s), c = exp2f(m - mn), p = exp2f(s - mn);
        l = l * c + p;
#pragma unroll
        for (int d = 0; d < 20; d++) o[d] = o[d] * c + p * __bfloat162float(kv[j * 40 + 20 + d]);
        m = mn;
      }
      float mg = m;
#pragma unroll
      for (int of = 16; of; of >>= 1) mg = fmaxf(mg, __shfl_xor_sync(~0u, mg, of));
      const float c = exp2f(m - mg);
      l *= c;
#pragma unroll
      for (int of = 16; of; of >>= 1) l += __shfl_xor_sync(~0u, l, of);
      const float sc = (1.f - __ldcg(g_gate + row)) / l;
#pragma unroll
      for (int d = 0; d < 20; d++) {
        float v = o[d] * c;
#pragma unroll
        for (int of = 16; of; of >>= 1) v += __shfl_xor_sync(~0u, v, of);
        const int col = h * 20 + d;
        if (lane == 0) *(__nv_bfloat16*)(g_o + ((size_t)(row >> 7) * 160 + 80 + (col >> 3)) * 2048 + (row & 127) * 16 + (col & 7) * 2) = __float2bfloat16(v * sc);
      }
    }
  }
  bar_sync(12, 256);
}

__device__ __forceinline__ void prep_q(uint8_t* sm, uint32_t sb, int i, int odd) {
  const uint32_t st = ((const uint32_t*)(sm + SM_RED))[i & 31];
  const float kn2 = __uint_as_float(__reduce_max_sync(~0u, (i & 16) ? 0u : st)), vmx = __uint_as_float(__reduce_max_sync(~0u, (i & 16) ? st : 0u));
  const bool head_ok = kn2 <= 1048576.f && vmx <= 32768.f && vmx >= 0.00390625f;
#pragma unroll
  for (int u = 0; u < 2; u++) {
    const int row = i + 256 * u;
    const uint32_t ad = sb + SM_Q + (row >> 7) * SLICE + (row & 127) * 16;
    const uint4 c0 = lds128(ad), c1 = lds128(ad + 2048), c2 = lds128(ad + 4096);
    const uint32_t v[12] = {c0.x, c0.y, c0.z, c0.w, c1.x, c1.y, c1.z, c1.w, c2.x, c2.y, c2.z, c2.w};
    float n0 = 0.f, n1 = 0.f;
#pragma unroll
    for (int c = 0; c < 12; c++) { const float2 a = __half22float2(*(const __half2*)&v[c]); n0 = fmaf(a.x, a.x, n0); n1 = fmaf(a.y, a.y, n1); }
    n0 += n1;
    float r;
    asm("sqrt.approx.f32 %0, %1;" : "=f"(r) : "f"(n0 * kn2));
    const float b = r * 1.01f + 0.05f;
    *(uint32_t*)(sm + SM_Q + (row >> 7) * SLICE + 4096 + (row & 127) * 16 + (odd ? 0 : 8)) = pack_h(-fmaxf(0.f, ceilf(b * 8.f - 126.f) * 0.125f), 13.5f);
    if (!(head_ok && b <= 30.f && n0 <= 1048576.f)) ((volatile uint32_t*)(sm + SM_FLAG))[row >> 4] = 1;
  }
}

struct Params {
  CUtensorMap tmX, tmWB, tmWA, tmOut;
  const __nv_bfloat16 *x, *gate_w, *w_phi, *wB, *woA, *woB;
};

__device__ __forceinline__ void agent_g(const Params& P, uint32_t sb) {
  const int bid = blockIdx.x, rank = bid & 1, lane = threadIdx.x & 31;
  const int pr = bid >> 1, rt = (pr & 7) * 2 + rank, ct = pr >> 3, h = bid >> 2, part = bid & 3;
  {
    int s = 2, ph = 0;
#pragma unroll 1
    for (int it = 6; it < 40; it++) {
      const int kb = it >= 20 ? it - 20 : it;
      const uint32_t st = sb + (s >> 1) * G_PB + G_XB + (s & 1) * G_WB + rank * 8192, fb = sb + B_FULL + 8 * s;
      const CUtensorMap* wm = it >= 20 ? &P.tmWA : &P.tmWB;
      mbar_wait_z(sb + B_EMPTY + 8 * s, ph);
      if (elect_one()) {
        mbar_expect_tx(fb, (s & 1) ? G_WB : G_XB + G_WB);
        if (s & 1) tma2d(sb + (s >> 1) * G_PB, &P.tmX, (kb - 1) * 32, rt * 128, fb - 8);
        tma2d_mc(st, wm, ct * 240 + rank * 128, kb * 32, fb, 3);
        tma2d_mc(st + 4096, wm, ct * 240 + rank * 128 + 64, kb * 32, fb, 3);
      }
      if (s == 1) ph ^= 1;
      if (++s == 6) s = 0;
    }
  }
  const uint8_t* kvsrc = g_kvB + (size_t)h * 16 * KVB;
  await(C_B, 128);
  mbar_wait_z(sb + B_EMPTY + 8, 1);
  if (elect_one()) {
    fence_async_g();
    mbar_expect_tx(sb + B_BD, 4 * SLICE + 2048 + 128);
    bulk_g2s(sb + SM_Q, g_qB + ((size_t)h * 16 + part * 4) * SLICE, 4 * SLICE, sb + B_BD);
    bulk_g2s(sb + SM_RED, g_stat + h * 32, 128, sb + B_BD);
    bulk_g2s(sb + SM_GATE, g_gate + part * 512, 2048, sb + B_BD);
#pragma unroll
    for (int j = 0; j < 1; j++) { mbar_expect_tx(sb + B_KV, 2 * KVB); bulk_g2s(sb + KV0, kvsrc, 2 * KVB, sb + B_KV); }
  }
#pragma unroll
  for (int q = 1; q < 3; q++) {
    mbar_wait_z(sb + B_EMPTY + 16 * q + 8, 0);
    if (elect_one()) {
#pragma unroll
      for (int j = 4 * q - 2; j < 4 * q + 2; j += 2) { mbar_expect_tx(sb + B_KV + 8 * j, 2 * KVB); bulk_g2s(sb + KV0 + j * KVB, kvsrc + j * KVB, 2 * KVB, sb + B_KV + 8 * j); }
    }
  }
  bar_sync(9, 288);
  if (lane == 0) {
#pragma unroll
    for (int q = 0; q < 12; q++) bulk_s2g(g_A + ((size_t)(ct * 12 + q) * 16 + rt) * SLICE, sb + SM_STG + q * SLICE, SLICE);
    bulk_commit();
    bulk_wait_all();
  }
  __syncwarp();
  if (elect_one()) {
#pragma unroll
    for (int j = 10; j < 16; j += 2) { mbar_expect_tx(sb + B_KV + 8 * j, 2 * KVB); bulk_g2s(sb + KV0 + j * KVB, kvsrc + j * KVB, 2 * KVB, sb + B_KV + 8 * j); }
  }
  if (lane == 0) signal(C_A + bid * 8);
  {
    const int l12 = lane % 12, c2 = ((l12 >> 2) * 32 + h) / 12, r2 = part * 4 + (l12 & 3);
    await_all(C_A + (((c2 * 8 + (r2 >> 1)) << 1) | (r2 & 1)) * 8, 1);
  }
  mbar_wait_z(sb + B_P + 16 * 2, 0);
  if (elect_one()) {
    fence_async_g();
    mbar_expect_tx(sb + B_AV, 8 * SLICE);
#pragma unroll
    for (int q = 0; q < 4; q++) {
      bulk_g2s(sb + KV0 + q * KVB + SLICE, g_A + ((size_t)(H_ + h) * 16 + part * 4 + q) * SLICE, SLICE, sb + B_AV);
      bulk_g2s(sb + KV0 + q * KVB, g_A + ((size_t)(2 * H_ + h) * 16 + part * 4 + q) * SLICE, SLICE, sb + B_AV);
    }
  }
  mbar_wait_z(sb + B_P + 16 * 3, 0);
}

__device__ __forceinline__ void branch_a(uint8_t* sm, uint32_t sb) {
  const int tid = fresh_tid(), bid = fresh_bid(), lane = tid & 31, g = lane >> 2, t = lane & 3;
  const int wp = __shfl_sync(~0u, (tid >> 5) & 3, 0), h = bid >> 2, part = bid & 3;
  const uint32_t sl = sb & 0x3FFFF, wphi16 = (sl + SM_WPHI) >> 4;
  const uint32_t zero = *(volatile uint32_t*)(sm + SM_ZERO);
  {
    const uint32_t ad = sb + SM_PHI + (wp * 2 + ((lane >> 3) & 1)) * 640 + (lane >> 4) * 128 + (lane & 7) * 16;
    const uint32_t ind16 = (sl + SM_IND) >> 4;
    float* dst = g_kvs + h * 960 + (wp * 16 + g) * 24 + 2 * t;
    mbar_wait_z(sb + B_AV, 0);
    float d[12];
    wg_fence();
    phi_logits(d, (sl + KV0 + SLICE) >> 4, wphi16);
    wg_commit();
    wg_wait<0>();
#pragma unroll 1
    for (int i = 0; i < 8; i++) {
      const uint32_t unit = sl + KV0 + (i >> 1) * KVB, buf = (i & 3) * 5120;
      {
        uint32_t e[12];
        phi_exp(e, d, t, zero);
        float z[4];
        const int nx = min(i + 1, 7);
        wg_fence();
        mma_b8_rs0(z, e, mkdesc(ind16, 128, 128, 0));
        mma_b8_rs(z, e + 4, mkdesc(ind16 + 16, 128, 128, 0));
        mma_b8_rs(z, e + 8, mkdesc(ind16 + 24, 128, 128, 0));
        phi_logits(d, (sl + KV0 + (nx >> 1) * KVB + SLICE + (nx & 1) * 1024) >> 4, wphi16);
        wg_commit();
        wg_wait<0>();
        fence_f<4>(z); fence_u<12>(e);
        uint32_t r[2];
#pragma unroll
        for (int hf = 0; hf < 2; hf++) r[hf] = __shfl_sync(~0u, pack_b(__fdividef(1.f, z[2 * hf]), __fdividef(1.f, z[2 * hf + 1])), lane & ~3);
        const uint32_t p0 = __byte_perm(r[0], 0, 0x1010), p1 = __byte_perm(r[1], 0, 0x1010), n0 = __byte_perm(r[0], 0, 0x3232), n1 = __byte_perm(r[1], 0, 0x3232);
        stsm4(ad + buf, mul_b2(e[0], p0), mul_b2(e[1], p1), mul_b2(e[2], p0), mul_b2(e[3], p1));
        stsm4(ad + buf + 256, mul_b2(e[4], t < 2 ? p0 : n0), mul_b2(e[5], t < 2 ? p1 : n1), mul_b2(e[6], n0), mul_b2(e[7], n1));
        stsm2(ad + buf + 512, mul_b2(e[10], n0), mul_b2(e[11], n1));
      }
      if ((i & 3) == 3) {
        fence_async();
        bar_sync(11, 128);
        float kv[12];
        wg_fence();
        mma_b24_tt0(kv, mkdesc((sl + SM_PHI) >> 4, 640, 128, 0), mkdesc((unit - KVB) >> 4, 384, 128, 0));
#pragma unroll
        for (int k = 1; k < 16; k++)
          mma_b24_tt(kv, mkdesc(((sl + SM_PHI) >> 4) + k * 80, 640, 128, 0), mkdesc(((unit - KVB + (k >> 3) * KVB) >> 4) + (k & 7) * 48, 384, 128, 0));
        wg_commit();
        wg_wait<0>();
        fence_f<12>(kv);
        if (wp < 3) {
#pragma unroll
          for (int c = 0; c < 3; c++) asm volatile("red.relaxed.gpu.global.add.v2.f32 [%0], {%1,%2};" ::"l"(dst + 8 * c), "f"(kv[4 * c]), "f"(kv[4 * c + 1]) : "memory");
        }
        if (wp < 2) {
#pragma unroll
          for (int c = 0; c < 3; c++) asm volatile("red.relaxed.gpu.global.add.v2.f32 [%0], {%1,%2};" ::"l"(dst + 192 + 8 * c), "f"(kv[4 * c + 2]), "f"(kv[4 * c + 3]) : "memory");
        }
        if (i == 3) bar_sync(11, 128);
      }
    }
    bar_sync(11, 128);
    if (tid == 608) signal(C_KV + h * 32);
    if (wp == 0) {
      if (elect_one()) {
        const uint8_t* kvsrc = g_kvB + (size_t)h * 16 * KVB;
#pragma unroll
        for (int j = 4; j >= 0; j -= 2) { mbar_expect_tx(sb + B_KV + 240 - 8 * j, 2 * KVB); bulk_g2s(sb + KV0 + j * KVB, kvsrc + j * KVB, 2 * KVB, sb + B_KV + 240 - 8 * j); }
      }
      mbar_wait_z(sb + B_P + 16 * 9, 0);
      if (elect_one()) {
        mbar_expect_tx(sb + B_AQ, 4 * SLICE);
        bulk_g2s(sb + SM_AQ, g_A + ((size_t)h * 16 + part * 4) * SLICE, 4 * SLICE, sb + B_AQ);
      }
      await(C_KV + h * 32, 4);
    }
    bar_sync(11, 128);
  }
  const int zc = (h & 1) ? 16 : 20;
#pragma unroll
  for (int u = 0; u < 2; u++) {
    const int j = (tid & 127) + 128 * u, fc = j / 48, n = j % 48, dd = n % 24;
    if (j < 240) {
      const float* kvs = g_kvs + h * 960 + fc * 192 + dd;
      uint32_t w[4];
#pragma unroll
      for (int c = 0; c < 4; c++) w[c] = dd == zc + 1 ? 0x3F803F80u : pack_b(__ldcg(kvs + 48 * c), __ldcg(kvs + 48 * c + 24));
      const bool neg = n >= 24, k0 = (fc > 2) == neg, k1 = (fc > 1) == neg;
      *(uint4*)(sm + SM_KVI + j * 16) = make_uint4(k0 ? w[0] : 0u, k0 ? w[1] : 0u, k1 ? w[2] : 0u, k1 ? w[3] : 0u);
    }
  }
  fence_async();
  __syncwarp();
  if (lane == 0) mbar_arrive(sb + B_KD);
}

__device__ __forceinline__ void agent_t(uint32_t sb) {
  const int bid = fresh_bid(), rank = bid & 1, lane = fresh_tid() & 31, part = bid & 3;
  mbar_wait_z(sb + B_QD, 0);
  if (lane == 0) signal(C_OA + part * 32);
  const uint8_t* osrc = g_o + (size_t)(bid >> 3) * 160 * 2048;
  const uint8_t* wsrc = g_wo + (bid & 7) * 204800;
  await(C_OA + (bid >> 5) * 32, 32);
  mbar_wait_z(sb + B_P + 16 * 13, 0);
  if (elect_one()) {
    fence_async_g();
#pragma unroll
    for (int it = 0; it < 4; it++) {
      mbar_expect_tx(sb + B_OF + 8 * it, O_STB);
      bulk_g2s(sb + o_slot(it) + O_AB, wsrc + it * O_WB, O_WB, sb + B_OF + 8 * it);
      bulk_g2s(sb + o_slot(it), osrc + it * O_AB, O_AB, sb + B_OF + 8 * it);
    }
  }
  mbar_wait_z(sb + B_P + 16 * 15, 0);
  if (elect_one()) {
#pragma unroll
    for (int it = 4; it < 6; it++) {
      mbar_expect_tx(sb + B_OF + 8 * it, O_STB);
      bulk_g2s(sb + o_slot(it) + O_AB, wsrc + it * O_WB, O_WB, sb + B_OF + 8 * it);
      bulk_g2s(sb + o_slot(it), osrc + it * O_AB, O_AB, sb + B_OF + 8 * it);
    }
  }
#pragma unroll
  for (int it = 6; it < 13; it++) {
    const uint32_t st = sb + o_slot(it & 7), fb = sb + B_OF + 8 * (it & 7);
    mbar_wait_z(sb + B_OE + 8 * (it & 7), it >= 14);
    if (elect_one()) {
      mbar_expect_tx(fb, O_STB);
      if (it < 10) bulk_g2s_mc(st + rank * 8192, osrc + it * O_AB + rank * 8192, 8192, fb, 3);
      bulk_g2s(st + O_AB, wsrc + it * O_WB, O_WB, fb);
    }
  }
  const int ob = C_OB + (bid >> 5) * 8 + lane * 32;
  uint32_t ready = 0;
#pragma unroll
  for (int it = 10; it < 20; it++) {
    const uint32_t st = sb + o_slot(it & 7), fb = sb + B_OF + 8 * (it & 7);
    const int h0 = (it - 10) * 64 / 20, h1 = ((it - 10) * 64 + 63) / 20;
    const uint32_t need = (uint32_t)((2ull << h1) - (1ull << h0));
    if (it >= 13) {
      mbar_wait(sb + B_OE + 8 * (it & 7), it >= 14);
      if (elect_one()) { mbar_expect_tx(fb, O_STB); bulk_g2s(st + O_AB, wsrc + it * O_WB, O_WB, fb); }
    }
    if ((ready & need) != need) { ready = await_mask(ob, need); fence_async_g(); }
    if (elect_one()) {
      bulk_g2s_mc(st + rank * 8192, osrc + it * O_AB + rank * 8192, 8192, fb, 3);
    }
  }
  uint32_t v = 0;
  if (lane == 0) v = atomicAdd(&g_cnt[C_EXIT], 1u);
  if (__shfl_sync(~0u, v, 0) == 127u) {
    g_cnt[C_KV + 32 * lane] = 0;
    if (lane < 7) g_cnt[32 * lane] = 0;
#pragma unroll
    for (int i = 0; i < 4; i++) { g_cnt[C_A + 8 * (lane + 32 * i)] = 0; g_cnt[C_OB + 8 * (lane + 32 * i)] = 0; }
  }
}

__global__ void __cluster_dims__(2, 1, 1) __launch_bounds__(640, 1) fused_kernel(const __grid_constant__ Params P) {
  extern __shared__ __align__(1024) uint8_t sm[];
  const uint32_t sb = __shfl_sync(~0u, smem_u32(sm), 0), sl = sb & 0x3FFFF;
  const int tid = fresh_tid(), wg = __shfl_sync(~0u, tid >> 7, 0), wp = __shfl_sync(~0u, (tid >> 5) & 3, 0), lane = tid & 31;
  const int bid = blockIdx.x;
  if (wg == 4 && wp == 0) {
    const int rank = bid & 1, rt = ((bid >> 1) & 7) * 2 + rank, ct = bid >> 4;
    if (elect_one()) {
      asm volatile("prefetch.tensormap [%0];" ::"l"(&P.tmWB) : "memory");
#pragma unroll
      for (int i = 0; i < 6; i++) mbar_init(sb + B_FULL + 8 * i, 1);
#pragma unroll
      for (int it = 0; it < 6; it++) {
        const int s = (it + 2) % 6;
        mbar_expect_tx(sb + B_FULL + 8 * s, (it & 1) ? G_WB : G_XB + G_WB);
        if (!(it & 1)) tma2d(sb + (s >> 1) * G_PB, &P.tmX, it * 32, rt * 128, sb + B_FULL + 8 * s);
      }
#pragma unroll
      for (int i = 0; i < 6; i++) mbar_init(sb + B_EMPTY + 8 * i, 4);
      mbar_init(sb + B_BD, 1); mbar_init(sb + B_QR, 8);
      asm volatile("fence.mbarrier_init.release.cluster;" ::: "memory");
    }
    __syncwarp();
    asm volatile("barrier.cluster.arrive.relaxed.aligned;" ::: "memory");
    asm volatile("barrier.cluster.wait.aligned;" ::: "memory");
    if (elect_one()) {
#pragma unroll
      for (int it = 0; it < 6; it++) {
        const int s = (it + 2) % 6;
        const uint32_t st = sb + (s >> 1) * G_PB + G_XB + (s & 1) * G_WB + rank * 8192, fb = sb + B_FULL + 8 * s;
        tma2d_mc(st, &P.tmWB, ct * 240 + rank * 128, it * 32, fb, 3);
        tma2d_mc(st + 4096, &P.tmWB, ct * 240 + rank * 128 + 64, it * 32, fb, 3);
      }
      asm volatile("prefetch.tensormap [%0];" ::"l"(&P.tmWA) : "memory");
    }
    __syncwarp();
  } else {
    asm volatile("barrier.cluster.arrive.relaxed.aligned;" ::: "memory");
    asm volatile("barrier.cluster.wait.aligned;" ::: "memory");
  }
  if (wg == 4) {
    asm volatile("setmaxnreg.dec.sync.aligned.u32 32;");
    if (wp == 0) agent_g(P, sb);
    bar_sync(11, 128);
    asm volatile("setmaxnreg.inc.sync.aligned.u32 64;");
    branch_a(sm, sb);
    if (wp == 0) agent_t(sb);
    return;
  }
  {
    const int pr = bid >> 1, rt = (pr & 7) * 2 + (bid & 1), ct = pr >> 3;
    const int h = bid >> 2, part = bid & 3, odd = h & 1;
    const uint32_t stg = sb + SM_STG;
    if (wg < 2) {
      asm volatile("setmaxnreg.inc.sync.aligned.u32 168;");
      float acc[120];
      int s = 2, ph = 0;
#pragma unroll 1
      for (int round = 0; round < 2; round++) {
        int prev = 0;
#pragma unroll 1
        for (int kb = 0; kb < 20; kb++) {
          mbar_wait(sb + B_FULL + 8 * s, ph);
          const uint32_t xa = (sl + (s >> 1) * G_PB + wg * 8192 + (s & 1) * 64) >> 4, wa = (sl + (s >> 1) * G_PB + G_XB + (s & 1) * G_WB) >> 4;
          wg_fence();
#pragma unroll
          for (int k = 0; k < 2; k++) {
            mma_n128(acc, mkdesc(xa + 2 * k, 16, 1024, 1), mkdesc(wa + 128 * k, 4096, 1024, 1), (kb | k) != 0);
            mma_n112(acc + 64, mkdesc(xa + 2 * k, 16, 1024, 1), mkdesc(wa + 512 + 128 * k, 4096, 1024, 1), (kb | k) != 0);
          }
          wg_commit();
          if (kb > 0) {
            wg_wait<1>();
            if ((tid & 127) < 2) mbar_arrive_cluster(sb + B_EMPTY + 8 * prev, tid & 1);
          }
          prev = s;
          if (s == 1) ph ^= 1;
          if (++s == 6) s = 0;
        }
        wg_wait<0>();
        fence_f<120>(acc);
        if ((tid & 127) < 2) mbar_arrive_cluster(sb + B_EMPTY + 8 * prev, tid & 1);
        if (round == 0) {
          g_epilogue<true>(acc, stg, ct, wg, wp, lane);
          fence_async();
          bar_arrive(1, 416);
        } else {
          bar_sync(2, 416);
          g_epilogue<false>(acc, stg, ct, wg, wp, lane);
          fence_async();
          bar_arrive(9, 288);
        }
      }
      asm volatile("setmaxnreg.dec.sync.aligned.u32 104;");
    } else {
      asm volatile("setmaxnreg.dec.sync.aligned.u32 56;");
      const int i8 = tid - 256;
      {
        uint4 v[4];
        uint32_t off[4];
#pragma unroll
        for (int u = 0; u < 4; u++) {
          const uint32_t c = bid * 100 + min((i8 >> 3) + 32 * u, 99), grp = c / 80, pc = c - grp * 80, k = grp * 8 + (i8 & 7), cb = pc / 10;
          v[u] = __ldg((const uint4*)(k < 640 ? P.woA + k * 640 : P.woB + (k - 640) * 640) + pc);
          off[u] = cb * (204800 - 1280) + pc * 128 + grp * 1280 + (i8 & 7) * 16;
        }
        if (wg == 2 && wp < 3) {
          const int kc = i8 / 24, f = i8 - kc * 24, d0 = kc == 3 ? (odd ? -4 : 16) : kc * 8 + odd * 4;
          const uint16_t* wsrc = (const uint16_t*)P.w_phi + h * 400 + d0 * 20 + (f < 20 ? f : f - 4);
          const bool lo = kc < 2 || (kc == 3 && !odd), hi = kc < 2 || (kc == 3 && odd);
          uint32_t w[8];
#pragma unroll
          for (int e = 0; e < 8; e++) w[e] = (e < 4 ? lo : hi) ? __ldg(wsrc + e * 20) : 0u;
          *(uint4*)(sm + SM_WPHI + i8 * 16) = make_uint4(w[0] | w[1] << 16, w[2] | w[3] << 16, w[4] | w[5] << 16, w[6] | w[7] << 16);
        } else if (wg == 2) {
          ((uint32_t*)(sm + SM_FLAG))[i8 - 96] = 0;
          if (elect_one()) {
#pragma unroll
            for (int i = 0; i < 32; i++) mbar_init(sb + B_KV + 8 * i, 1);
#pragma unroll
            for (int i = 16; i < 26; i++) mbar_arrive(sb + B_KV + 8 * i);
            mbar_init(sb + B_AV, 1); mbar_init(sb + B_AQ, 1); mbar_init(sb + B_KD, 4); mbar_init(sb + B_QD, 16);
#pragma unroll
            for (int i = 0; i < 16; i++) mbar_init(sb + B_P + 16 * i, 16);
#pragma unroll
            for (int i = 0; i < 8; i++) { mbar_init(sb + B_OF + 8 * i, 1); mbar_init(sb + B_OE + 8 * i, 4); }
            asm volatile("fence.mbarrier_init.release.cluster;" ::: "memory");
          }
        } else {
          const int t7 = i8 - 128;
          ((uint2*)(sm + SM_ZERO))[t7] = make_uint2(0u, 0u);
          if (t7 < 80) {
            const int fc = t7 >> 4, n = (t7 >> 1) & 7, neg = (t7 & 1) ? fc > 1 : fc > 2;
            const uint32_t w = n == neg ? 0x3F803F80u : 0u;
            ((uint2*)(sm + SM_IND))[t7] = make_uint2(w, w);
          }
        }
        if (part == 0 && i8 < 240) ((float4*)g_kvs)[h * 240 + i8] = make_float4(0.f, 0.f, 0.f, 0.f);
        fence_async();
#pragma unroll
        for (int u = 0; u < 4; u++) *(uint4*)(g_wo + off[u]) = v[u];
      }
      {
        const int row = bid * 16 + (i8 >> 5) * 2;
        float z0 = 0.f, z1 = 0.f;
#pragma unroll
        for (int i = 0; i < 3; i++) {
          if (lane + 32 * i < 80) {
            const uint4 gw = __ldg((const uint4*)P.gate_w + lane + 32 * i);
            const uint4 a = __ldg((const uint4*)(P.x + row * D_) + lane + 32 * i), b = __ldg((const uint4*)(P.x + (row + 1) * D_) + lane + 32 * i);
            const uint32_t gv[4] = {gw.x, gw.y, gw.z, gw.w}, av[4] = {a.x, a.y, a.z, a.w}, bv[4] = {b.x, b.y, b.z, b.w};
#pragma unroll
            for (int e = 0; e < 4; e++) {
              const float gl = bf_lo(gv[e]), gh = bf_hi(gv[e]);
              z0 = fmaf(bf_lo(av[e]), gl, fmaf(bf_hi(av[e]), gh, z0));
              z1 = fmaf(bf_lo(bv[e]), gl, fmaf(bf_hi(bv[e]), gh, z1));
            }
          }
        }
        float z = (lane & 1) ? z1 : z0;
        z += __shfl_xor_sync(~0u, (lane & 1) ? z0 : z1, 1);
#pragma unroll
        for (int o = 16; o > 1; o >>= 1) z += __shfl_xor_sync(~0u, z, o);
        if (lane < 2) g_gate[row + lane] = __fdividef(1.f, 1.f + __expf(-z));
      }
      if (wg == 3) {
        const int t7 = tid & 127;
        bar_sync(1, 416);
        const bool pl = (PMASK >> (t7 >> 3)) & 1;
#pragma unroll 2
        for (int q = 0; q < 12; q++) {
          const int sidx = ct * 12 + q, type = sidx >> 5;
          if (type == 0) continue;
          const uint32_t ad = stg + q * SLICE + (type == 1 ? t7 * 16 : (t7 >> 3) * 384 + (t7 & 7) * 16), cs = type == 1 ? 2048 : 128;
          const uint4 c0 = lds128(ad), c1 = lds128(ad + cs), c2 = lds128(ad + 2 * cs);
          const uint32_t v[10] = {c0.x, c0.y, c0.z, c0.w, c1.x, c1.y, c1.z, c1.w, (q & 1) ? c2.z : c2.x, (q & 1) ? c2.w : c2.y};
          float r;
          if (type == 1) {
            float r1 = 0.f;
            r = 0.f;
#pragma unroll
            for (int i = 0; i < 10; i++) { const float2 f = __half22float2(*(const __half2*)&v[i]); r = fmaf(f.x, f.x, r); r1 = fmaf(f.y, f.y, r1); }
            r += r1;
            if (pl) r *= 262144.f;
          } else {
            uint32_t m = 0;
#pragma unroll
            for (int i = 0; i < 10; i++) m = __vmaxu2(m, v[i] & 0x7fff7fffu);
            m = max(m & 0xffffu, m >> 16);
            r = __half2float(__ushort_as_half((unsigned short)m));
          }
          const uint32_t u = __reduce_max_sync(~0u, __float_as_uint(r));
          if (lane == 0) ((uint32_t*)(sm + SM_RED))[q * 4 + wp] = u;
        }
        bar_arrive(2, 416);
        bar_sync(7, 128);
        if (t7 < 12) {
          const int sidx = ct * 12 + t7, type = sidx >> 5, head = sidx & 31;
          const uint4 u = *(const uint4*)(sm + SM_RED + t7 * 16);
          if (type != 0) g_stat[head * 32 + (type - 1) * 16 + rt] = __uint_as_float(max(max(u.x, u.y), max(u.z, u.w)));
        }
        fence_async();
        bar_arrive(3, 256);
      } else if (wp == 1) {
        bar_sync(1, 416);
        if (lane == 0) {
#pragma unroll 1
          for (int q = 0; q < 12; q++) {
            const int sidx = ct * 12 + q, type = sidx >> 5, head = sidx & 31;
            bulk_s2g(type == 0 ? g_qB + ((size_t)head * 16 + rt) * SLICE : g_kvB + ((size_t)head * 16 + rt) * KVB + (type - 1) * SLICE, stg + q * SLICE, SLICE);
            bulk_commit();
            asm volatile("cp.async.bulk.wait_group 1;" ::: "memory");
          }
          bulk_wait_all();
        }
        __syncwarp();
        bar_arrive(2, 416);
        bar_sync(3, 256);
        if (lane == 0) signal(C_B);
        __syncwarp();
      } else {
        bar_arrive(3, 256);
      }
      mbar_wait_z(sb + B_BD, 0);
      prep_q(sm, sb, tid - 256, odd);
      fence_async();
      __syncwarp();
      if (lane == 0) mbar_arrive(sb + B_QR);
      asm volatile("setmaxnreg.inc.sync.aligned.u32 104;");
    }
  }
  uint32_t oh[6], s[32], p[32];
  float o[12];
  mbar_wait_z(sb + B_QR, 0);
  const uint32_t zero = *(volatile uint32_t*)(sm + SM_ZERO);
#pragma unroll
  for (int i = 0; i < 12; i++) o[i] = 0.f;
  const uint32_t stops = 0x8480u;
#pragma unroll 1
  for (int j0 = 0; j0 < 16;) {
    const int jj = j0 + __ffs(stops >> j0) - 1;
    uint32_t bar = sb + B_KV + 16 * j0;
    const uint32_t k16 = (sl + KV0 + (j0 < 8 ? 2 * j0 : 31 - 2 * j0) * KVB) >> 4;
    const uint32_t qoff = SM_Q + wg * SLICE + (j0 >> 3) * 1024;
    const uint64_t dq0 = mkdesc((sl + qoff) >> 4, 2048, 128, 0), dq1 = mkdesc((sl + qoff + 4096) >> 4, SM_ZERO - 4096 - qoff, 128, 0);
    uint64_t dk0 = mkdesc(k16, 2048, 128, 0), dk1 = mkdesc(k16 + 256, 2048, 128, 0), dv[4];
#pragma unroll
    for (int i = 0; i < 4; i++) dv[i] = mkdesc(k16 + ((SLICE + i * 768) >> 4), 384, 128, 0);
#pragma unroll
    for (int i = 0; i < 6; i++) oh[i] = 0;
    fence_u<6>(oh);
    const uint32_t inc = j0 < 8 ? (KVB >> 4) : -(KVB >> 4), inc2 = inc - 192;
#pragma unroll 1
    for (; j0 <= jj; j0++)
#pragma unroll
      for (int u = 0; u < 2; u++) {
        if (u == 0) { mbar_wait_u(bar, 0); bar += 16; }
        wg_fence();
        mma_qk_first(s, dq0, dk0); mma_qk_acc(s, dq1, dk1);
        wg_commit();
        dk0 = addlo_r(dk0, inc); dk1 = addlo_r(dk1, inc);
        wg_wait<0>();
        fence_u<32>(s);
        if (u == 0 && elect_one()) mbar_arrive(bar + (B_P - B_KV - 16));
#pragma unroll
        for (int hf = 0; hf < 2; hf++) {
#pragma unroll
          for (int i = hf * 6; i < (hf ? 16 : 6); i++) {
            if ((PMASK >> i) & 1) { p[2 * i] = exp_poly(s[2 * i], zero); p[2 * i + 1] = exp_poly(s[2 * i + 1], zero); }
            else { p[2 * i] = exp_mufu(s[2 * i]); p[2 * i + 1] = exp_mufu(s[2 * i + 1]); }
          }
          wg_fence();
#pragma unroll
          for (int i = hf * 3; i < (hf ? 8 : 3); i++) { mma_pv(oh, p + 4 * i, dv[i & 3]); dv[i & 3] = i < 4 ? addlo<192>(dv[i & 3]) : addlo_r(dv[i & 3], inc2); }
        }
        wg_commit();
      }
    wg_wait<0>();
    fence_u<6>(oh);
#pragma unroll
    for (int i = 0; i < 6; i++) { const float2 v = __half22float2(*(__half2*)&oh[i]); o[2 * i] += v.x; o[2 * i + 1] += v.y; }
    const int tid = fresh_tid(), bid = fresh_bid(), lane = tid & 31, g = lane >> 2, t = lane & 3;
    const int wg = __shfl_sync(~0u, tid >> 7, 0), wp = __shfl_sync(~0u, (tid >> 5) & 3, 0);
    const int h = bid >> 2, part = bid & 3, odd = h & 1, rloc = wg * 128 + wp * 16 + g;
    const float* gate = (const float*)(sm + SM_GATE) + rloc;
    const int src = (lane & ~3) | (odd ? 0 : 2);
    if ((jj & 7) == 7) {
      const float l0 = __shfl_sync(~0u, o[8], src), l1 = __shfl_sync(~0u, o[10], src);
      float chk = 0.f;
#pragma unroll
      for (int i = 0; i < 12; i++) chk += fabsf(o[i]);
      volatile uint32_t* flag = (volatile uint32_t*)(sm + SM_FLAG) + wg * 8 + (jj >> 3) * 4 + wp;
      const bool ok = *flag == 0 && l0 >= 32.f && l1 >= 32.f && chk < 1e30f;
      if (!__all_sync(~0u, ok)) { if (lane == 0) *flag = 1; }
      else {
        const float r0 = __fdividef(1.f - gate[(jj >> 3) * 64], l0), r1 = __fdividef(1.f - gate[(jj >> 3) * 64 + 8], l1);
        uint32_t v[6];
#pragma unroll
        for (int c = 0; c < 3; c++) { v[2 * c] = pack_b(o[4 * c] * r0, o[4 * c + 1] * r0); v[2 * c + 1] = pack_b(o[4 * c + 2] * r1, o[4 * c + 3] * r1); }
        store_o(v, 80, h, part * 512 + rloc + (jj >> 3) * 64, t);
      }
#pragma unroll
      for (int i = 0; i < 12; i++) o[i] = 0.f;
    } else {
      mbar_wait_z(sb + B_AQ, 0);
      const uint32_t kvi = (sl + SM_KVI) >> 4, img = (sl + SM_AQ + wg * SLICE) >> 4;
      mbar_wait_z(sb + B_KD, 0);
#pragma unroll 1
      for (int tl = 0; tl < 2; tl++) {
        float n[24];
        uint32_t e[12], v[6];
        float d[12];
        wg_fence();
        phi_logits(d, img + 64 * tl, (sl + SM_WPHI) >> 4);
        wg_commit();
        wg_wait<0>();
        phi_exp(e, d, t, zero);
        wg_fence();
        mma_b48_rs0(n, e, mkdesc(kvi, 768, 128, 0));
        mma_b48_rs(n, e + 4, mkdesc(kvi + 96, 768, 128, 0));
        mma_b48_rs(n, e + 8, mkdesc(kvi + 144, 768, 128, 0));
        wg_commit();
        wg_wait<0>();
        phi_out(v, n, gate + tl * 64, src);
        store_o(v, 0, h, part * 512 + rloc + tl * 64, t);
      }
      __syncwarp();
      if (lane == 0) mbar_arrive(sb + B_QD);
    }
    __syncwarp();
  }
  {
    const int tid = fresh_tid(), bid = fresh_bid(), lane = tid & 31;
    const int wg = __shfl_sync(~0u, tid >> 7, 0), wp = __shfl_sync(~0u, (tid >> 5) & 3, 0);
    if (wg >= 2) {
      bar_sync(8, 512);
      if (wg == 2 && tid < 264) mbar_arrive_cluster(sb + B_OE + 48 + (tid & 2) * 4, tid & 1);
      if (__any_sync(~0u, ((const uint32_t*)(sm + SM_FLAG))[lane] != 0)) attn_fallback((const uint32_t*)(sm + SM_FLAG), bid >> 2, bid & 3, P.x, P.wB);
      if (tid == 384) signal(C_OB + bid * 8);
    } else {
      bar_arrive(8, 512);
    }
    if (wg < 2) {
      float acc[40];
#pragma unroll 1
      for (int it = 0; it < 20; it++) {
        const int s = it & 7;
        bool rel = it > 0 && it <= 12;
        if (!mbar_test_wg(sb + B_OF + 8 * s, (it >> 3) & 1, 4 + wg)) {
          wg_wait<0>();
          if (rel && (tid & 127) < 2) mbar_arrive_cluster(sb + B_OE + 8 * ((it - 1) & 7), tid & 1);
          rel = false;
          mbar_wait(sb + B_OF + 8 * s, (it >> 3) & 1);
        }
        const uint32_t aa = (sl + o_slot(s) + wg * 1024) >> 4, wa = (sl + o_slot(s) + O_AB) >> 4;
        wg_fence();
#pragma unroll
        for (int k = 0; k < 4; k++) mma_n80(acc, mkdesc(aa + 256 * k, 2048, 128, 0), mkdesc(wa + 160 * k, 1280, 128, 0), (it | k) != 0);
        wg_commit();
        wg_wait<1>();
        if (rel && (tid & 127) < 2) mbar_arrive_cluster(sb + B_OE + 8 * ((it - 1) & 7), tid & 1);
      }
      wg_wait<0>();
      fence_f<40>(acc);
      const uint32_t stg = sb + o_slot(6) + wg * 10240;
      const uint32_t ad = stg + (wp * 16 + ((lane >> 3) & 1) * 8 + (lane & 7)) * 160 + (lane >> 4) * 16;
      bar_sync(1, 256);
#pragma unroll
      for (int i = 0; i < 5; i++)
        stsm4(ad + i * 32, pack_b(acc[8 * i], acc[8 * i + 1]), pack_b(acc[8 * i + 2], acc[8 * i + 3]), pack_b(acc[8 * i + 4], acc[8 * i + 5]), pack_b(acc[8 * i + 6], acc[8 * i + 7]));
      fence_async();
      bar_sync(4 + wg, 128);
      if ((tid & 127) == 0) {
        tma2d_store(&P.tmOut, stg, (bid & 7) * 80, (bid >> 3) * 128 + wg * 64);
        bulk_commit();
        asm volatile("cp.async.bulk.wait_group.read 0;" ::: "memory");
      }
    }
  }
}

typedef CUresult (*EncodeFn)(CUtensorMap*, CUtensorMapDataType, cuuint32_t, void*, const cuuint64_t*, const cuuint64_t*, const cuuint32_t*,
                             const cuuint32_t*, CUtensorMapInterleave, CUtensorMapSwizzle, CUtensorMapL2promotion, CUtensorMapFloatOOBfill);

void encode(EncodeFn fn, CUtensorMap* m, const void* p, int rank, const cuuint64_t* dims, const cuuint64_t* strides, const cuuint32_t* box, CUtensorMapSwizzle swz) {
  const cuuint32_t es[3] = {1, 1, 1};
  CUresult r = fn(m, CU_TENSOR_MAP_DATA_TYPE_BFLOAT16, rank, const_cast<void*>(p), dims, strides, box, es, CU_TENSOR_MAP_INTERLEAVE_NONE, swz,
                  CU_TENSOR_MAP_L2_PROMOTION_L2_256B, CU_TENSOR_MAP_FLOAT_OOB_FILL_NONE);
  if (r != CUDA_SUCCESS) fprintf(stderr, "tensor map encode failed: %d\n", (int)r);
}

}

extern "C" void kernel_launch(void* const* d_in, const int* in_sizes, int n_in, void* d_out, int out_size) {
  (void)in_sizes; (void)n_in; (void)out_size;
  static EncodeFn fn = nullptr;
  if (!fn) {
    void* p = nullptr;
    cudaDriverEntryPointQueryResult qr;
    cudaGetDriverEntryPoint("cuTensorMapEncodeTiled", &p, cudaEnableDefault, &qr);
    fn = (EncodeFn)p;
    cudaFuncSetAttribute(fused_kernel, cudaFuncAttributeMaxDynamicSharedMemorySize, SM_TOTAL);
  }
  Params P;
  P.x = (const __nv_bfloat16*)d_in[0];
  P.w_phi = (const __nv_bfloat16*)d_in[2];
  P.wB = (const __nv_bfloat16*)d_in[5];
  P.gate_w = (const __nv_bfloat16*)d_in[7];
  P.woA = (const __nv_bfloat16*)d_in[3];
  P.woB = (const __nv_bfloat16*)d_in[6];
  {
    const cuuint64_t d[2] = {640, 2048}, st[1] = {1280};
    const cuuint32_t box[2] = {64, 128}, obox[2] = {80, 64};
    encode(fn, &P.tmX, d_in[0], 2, d, st, box, CU_TENSOR_MAP_SWIZZLE_128B);
    encode(fn, &P.tmOut, d_out, 2, d, st, obox, CU_TENSOR_MAP_SWIZZLE_NONE);
  }
  {
    const cuuint64_t d[2] = {1920, 640}, st[1] = {3840};
    const cuuint32_t box[2] = {64, 32};
    encode(fn, &P.tmWA, d_in[1], 2, d, st, box, CU_TENSOR_MAP_SWIZZLE_128B);
    encode(fn, &P.tmWB, d_in[5], 2, d, st, box, CU_TENSOR_MAP_SWIZZLE_128B);
  }
  fused_kernel<<<128, 640, SM_TOTAL, cudaStreamPerThread>>>(P);
}
```
